```python
import torch

def _softmax(x, axis=-1):
    return torch.softmax(x, dim=axis)
def _gelu(x):
    return torch.nn.functional.gelu(x, approximate="tanh")
def _silu(x):
    return torch.nn.functional.silu(x)
def _sigmoid(x):
    return torch.sigmoid(x)
def _layernorm(x, axis=-1, eps=1e-5):
    m = x.mean(dim=axis, keepdim=True)
    v = x.var(dim=axis, keepdim=True, unbiased=False)
    return (x - m) / torch.sqrt(v + eps)
def _scatter_add(tgt, idx, src, axis=0):
    return tgt.clone().index_add_(axis, idx, src)
def _segment_sum(src, seg, n):
    out = torch.zeros((n,) + src.shape[1:], dtype=src.dtype)
    return out.index_add_(0, seg, src)
def _pad(x, pw):
    flat = tuple(v for pair in reversed(pw) for v in pair)
    return torch.nn.functional.pad(x, flat)

kernel_name = 'concat_heads__gqa_block_cached__gqa_block_cached__near_ridge'

def setup_inputs():

    _w = (lambda a: (lambda t: t.to(torch.bfloat16) if t.is_floating_point() else t)(torch.as_tensor(a)))
    def _A_setup():
        B, Sq, D = 8, 64, 512
        Hq, Hkv, Sk, Dh = 32, 8, 2048, 128
        assert Hq % Hkv == 0, (Hq, Hkv)
        return {
            "x": _w((lambda *s: torch.randn(*s, dtype=torch.bfloat16) * 0.8)(B, Sq, D)),
            "k_cache": _w((lambda *s: torch.randn(*s, dtype=torch.bfloat16) * 0.8)(B, Hkv, Sk, Dh)),
            "v_cache": _w((lambda *s: torch.randn(*s, dtype=torch.bfloat16) * 0.05)(B, Hkv, Sk, Dh)),
            "wq": _w((lambda *s: torch.randn(*s, dtype=torch.bfloat16) * 0.8)(D, Hq * Dh) * (D ** -0.5)),
            "wo": _w((lambda *s: torch.randn(*s, dtype=torch.bfloat16) * 0.05)(Hq * Dh, D) * ((Hq * Dh) ** -0.5)),
        }
    _A_in = _A_setup()

    def _B_setup():
        B, Sq, D = 8, 64, 512
        Hq, Hkv, Sk, Dh = 32, 8, 2048, 128
        assert Hq % Hkv == 0, (Hq, Hkv)
        return {
            "x": _w((lambda *s: torch.randn(*s, dtype=torch.bfloat16) * 0.8)(B, Sq, D)),
            "k_cache": _w((lambda *s: torch.randn(*s, dtype=torch.bfloat16) * 0.8)(B, Hkv, Sk, Dh)),
            "v_cache": _w((lambda *s: torch.randn(*s, dtype=torch.bfloat16) * 0.05)(B, Hkv, Sk, Dh)),
            "wq": _w((lambda *s: torch.randn(*s, dtype=torch.bfloat16) * 0.8)(D, Hq * Dh) * (D ** -0.5)),
            "wo": _w((lambda *s: torch.randn(*s, dtype=torch.bfloat16) * 0.05)(Hq * Dh, D) * ((Hq * Dh) ** -0.5)),
        }
    _B_in = _B_setup()

    return {
        "A_x": _A_in["x"],
        "A_k_cache": _A_in["k_cache"],
        "A_v_cache": _A_in["v_cache"],
        "A_wq": _A_in["wq"],
        "A_wo": _A_in["wo"],
        "B_x": _B_in["x"],
        "B_k_cache": _B_in["k_cache"],
        "B_v_cache": _B_in["v_cache"],
        "B_wq": _B_in["wq"],
        "B_wo": _B_in["wo"],
    }

def reference(A_x, A_k_cache, A_v_cache, A_wq, A_wo, B_x, B_k_cache, B_v_cache, B_wq, B_wo):
    def _A_ref(x, k_cache, v_cache, wq, wo):
        B, Sq, D = x.shape
        Hq, Dh = 32, 128
        Hkv = k_cache.shape[1]
        rep = Hq // Hkv
        q = (lambda x, *d: x.permute(*d))((x @ wq).reshape(B, Sq, Hq, Dh), 0, 2, 1, 3)
        k = (lambda x, n, axis: torch.repeat_interleave(x, n, dim=axis))(k_cache, rep, axis=1)
        v = (lambda x, n, axis: torch.repeat_interleave(x, n, dim=axis))(v_cache, rep, axis=1)
        scores = torch.einsum("bhqd,bhkd->bhqk", q, k) * (Dh ** -0.5)
        p = _softmax(scores, axis=-1)
        o = torch.einsum("bhqk,bhkd->bhqd", p, v)
        return (lambda x, *d: x.permute(*d))(o, 0, 2, 1, 3).reshape(B, Sq, Hq * Dh) @ wo

    def _B_ref(x, k_cache, v_cache, wq, wo):
        B, Sq, D = x.shape
        Hq, Dh = 32, 128
        Hkv = k_cache.shape[1]
        rep = Hq // Hkv
        q = (lambda x, *d: x.permute(*d))((x @ wq).reshape(B, Sq, Hq, Dh), 0, 2, 1, 3)
        k = (lambda x, n, axis: torch.repeat_interleave(x, n, dim=axis))(k_cache, rep, axis=1)
        v = (lambda x, n, axis: torch.repeat_interleave(x, n, dim=axis))(v_cache, rep, axis=1)
        scores = torch.einsum("bhqd,bhkd->bhqk", q, k) * (Dh ** -0.5)
        p = _softmax(scores, axis=-1)
        o = torch.einsum("bhqk,bhkd->bhqd", p, v)
        return (lambda x, *d: x.permute(*d))(o, 0, 2, 1, 3).reshape(B, Sq, Hq * Dh) @ wo

    a = _A_ref(A_x, A_k_cache, A_v_cache, A_wq, A_wo)
    b = _B_ref(B_x, B_k_cache, B_v_cache, B_wq, B_wo)
    return torch.concatenate([a, b], axis=-1)
```

```cpp
#include <cuda_runtime.h>
#include <cuda.h>
#include <cuda_bf16.h>
#include <stdint.h>

namespace {

constexpr int kB = 8, kSq = 64, kD = 512, kHq = 32, kHkv = 8, kSk = 2048, kDh = 128;
constexpr int kTileN = 128;
constexpr int kKvTiles = kSk / kTileN;
constexpr int kSlots = 5;
constexpr uint32_t kSlotBytes = 32768;
constexpr uint32_t kQBytes = 65536;
constexpr uint32_t kBarOff = kQBytes + kSlots * kSlotBytes;
constexpr uint32_t kSmemBytes = kBarOff + 512 + 2304;
constexpr int kWTiles = 16;
constexpr int kThreads = 256;
constexpr uint32_t kSpinLimit = 1u << 24;
constexpr uint32_t kPollLimit = 1u << 20;

struct Params {
    CUtensorMap maps[10];
};

__device__ uint4 g_inbox[128 * 8 * 4 * 128];
__device__ unsigned int g_epoch[128];

#define KVROW(x) (x)
#define STAMP(i) do {} while (0)
#define STEP(step, i) do {} while (0)

__device__ __forceinline__ uint32_t smem_u32(const void* p) { return (uint32_t)__cvta_generic_to_shared(p); }
__device__ __forceinline__ void mbar_init(uint32_t a, uint32_t c) { asm volatile("mbarrier.init.shared::cta.b64 [%0], %1;" ::"r"(a), "r"(c) : "memory"); }
__device__ __forceinline__ void mbar_expect_tx(uint32_t a, uint32_t b) { asm volatile("mbarrier.arrive.expect_tx.shared::cta.b64 _, [%0], %1;" ::"r"(a), "r"(b) : "memory"); }
__device__ __forceinline__ void mbar_arrive(uint32_t a) { asm volatile("mbarrier.arrive.shared::cta.b64 _, [%0];" ::"r"(a) : "memory"); }
__device__ __forceinline__ void mbar_wait(uint32_t a, uint32_t parity) {
    asm volatile(
        "{\n"
        ".reg .pred P;\n"
        ".reg .u32 n;\n"
        "mbarrier.try_wait.parity.shared::cta.b64 P, [%0], %1;\n"
        "@P bra DONE;\n"
        "mov.u32 n, 0;\n"
        "LOOP:\n"
        "mbarrier.try_wait.parity.shared::cta.b64 P, [%0], %1;\n"
        "@P bra DONE;\n"
        "add.u32 n, n, 1;\n"
        "setp.lt.u32 P, n, %2;\n"
        "@P bra LOOP;\n"
        "trap;\n"
        "DONE:\n"
        "}\n" ::"r"(a), "r"(parity), "n"(kSpinLimit) : "memory");
}
__device__ __forceinline__ void tma3d(uint32_t dst, const CUtensorMap* m, int c0, int c1, int c2, uint32_t bar) {
    asm volatile("cp.async.bulk.tensor.3d.shared::cluster.global.mbarrier::complete_tx::bytes [%0], [%1, {%3, %4, %5}], [%2];"
                 ::"r"(dst), "l"(m), "r"(bar), "r"(c0), "r"(c1), "r"(c2) : "memory");
}
__device__ __forceinline__ void tma3d_hint(uint32_t dst, const CUtensorMap* m, int c0, int c1, int c2, uint32_t bar, uint64_t pol) {
    asm volatile("cp.async.bulk.tensor.3d.shared::cluster.global.mbarrier::complete_tx::bytes.L2::cache_hint [%0], [%1, {%3, %4, %5}], [%2], %6;"
                 ::"r"(dst), "l"(m), "r"(bar), "r"(c0), "r"(c1), "r"(c2), "l"(pol) : "memory");
}
__device__ __forceinline__ void prefetch_l2(const void* src, uint32_t bytes) {
    asm volatile("cp.async.bulk.prefetch.L2.global [%0], %1;" ::"l"(src), "r"(bytes) : "memory");
}
__device__ __forceinline__ void prefetch_map(const CUtensorMap* m) { asm volatile("prefetch.tensormap [%0];" ::"l"(m) : "memory"); }
__device__ __forceinline__ bool elect_one() {
    uint32_t p;
    asm volatile("{\n.reg .pred P;\nelect.sync _|P, 0xffffffff;\nselp.b32 %0, 1, 0, P;\n}\n" : "=r"(p));
    return p != 0;
}
__device__ __forceinline__ void bar_sync(int id, int n) { asm volatile("bar.sync %0, %1;" ::"r"(id), "r"(n) : "memory"); }
__device__ __forceinline__ void bar_arrive(int id, int n) { asm volatile("bar.arrive %0, %1;" ::"r"(id), "r"(n) : "memory"); }
template <int ID0, int ID1, int N> __device__ __forceinline__ void bar_sync_sel(int sel) {
    asm volatile("{\n.reg .pred P;\nsetp.eq.s32 P, %0, 0;\n@P bar.sync %1, %3;\n@!P bar.sync %2, %3;\n}\n" ::"r"(sel), "n"(ID0), "n"(ID1), "n"(N) : "memory");
}
template <int ID0, int ID1, int N> __device__ __forceinline__ void bar_arrive_sel(int sel) {
    asm volatile("{\n.reg .pred P;\nsetp.eq.s32 P, %0, 0;\n@P bar.arrive %1, %3;\n@!P bar.arrive %2, %3;\n}\n" ::"r"(sel), "n"(ID0), "n"(ID1), "n"(N) : "memory");
}
__device__ __forceinline__ int cta_id() {
    int v;
    asm volatile("mov.u32 %0, %%ctaid.x;" : "=r"(v));
    return v;
}
__device__ __forceinline__ void fence_async_smem() { asm volatile("fence.proxy.async.shared::cta;" ::: "memory"); }
__device__ __forceinline__ void wg_fence() { asm volatile("wgmma.fence.sync.aligned;" ::: "memory"); }
__device__ __forceinline__ void wg_commit() { asm volatile("wgmma.commit_group.sync.aligned;" ::: "memory"); }
template <int N> __device__ __forceinline__ void wg_wait() { asm volatile("wgmma.wait_group.sync.aligned %0;" ::"n"(N) : "memory"); }
template <int N> __device__ __forceinline__ void reg_fence(float (&r)[N]) {
#pragma unroll
    for (int i = 0; i < N; i++) asm volatile("" : "+f"(r[i])::"memory");
}
template <int N> __device__ __forceinline__ void reg_fence(uint32_t (&r)[N]) {
#pragma unroll
    for (int i = 0; i < N; i++) asm volatile("" : "+r"(r[i])::"memory");
}
__device__ __forceinline__ uint32_t mkdesc(uint32_t addr, uint32_t lbo) { return (addr >> 4) | ((lbo >> 4) << 16); }
template <int N> __device__ __forceinline__ void sched_break(uint32_t never_all_ones, float (&s)[64]) {
    if (__builtin_expect(never_all_ones == 0xffffffffu, 0)) {
#pragma unroll
        for (int i = 0; i < N; i++) asm volatile("neg.f32 %0, %0;" : "+f"(s[i])::"memory");
    }
}
__device__ __forceinline__ uint32_t pack_bf16(float lo, float hi) {
    uint32_t r;
    asm("cvt.rn.bf16x2.f32 %0, %1, %2;" : "=r"(r) : "f"(hi), "f"(lo));
    return r;
}
__device__ __forceinline__ float ex2(float x) {
    float y;
    asm("ex2.approx.ftz.f32 %0, %1;" : "=f"(y) : "f"(x));
    return y;
}
__device__ __forceinline__ void st_packet(uint4* dst, uint32_t a, uint32_t b, uint32_t c, uint32_t d) {
    asm volatile("{\n.reg .b64 lo, hi;\n.reg .b128 v;\nmov.b64 lo, {%1, %2};\nmov.b64 hi, {%3, %4};\nmov.b128 v, {lo, hi};\n"
                 "st.relaxed.gpu.global.b128 [%0], v;\n}\n" ::"l"(dst), "r"(a), "r"(b), "r"(c), "r"(d) : "memory");
}
__device__ __forceinline__ uint4 ld_packet(const uint4* src) {
    uint4 r;
    asm volatile("{\n.reg .b64 lo, hi;\n.reg .b128 v;\nld.relaxed.gpu.global.b128 v, [%4];\nmov.b128 {lo, hi}, v;\n"
                 "mov.b64 {%0, %1}, lo;\nmov.b64 {%2, %3}, hi;\n}\n" : "=r"(r.x), "=r"(r.y), "=r"(r.z), "=r"(r.w) : "l"(src) : "memory");
    return r;
}
__device__ __forceinline__ void stmatrix_x4(uint32_t addr, uint32_t a, uint32_t b, uint32_t c, uint32_t d) {
    asm volatile("stmatrix.sync.aligned.m8n8.x4.shared.b16 [%0], {%1, %2, %3, %4};" ::"r"(addr), "r"(a), "r"(b), "r"(c), "r"(d) : "memory");
}

template <int OA, int OB>
__device__ __forceinline__ void wgmma_ss_n128(float (&d)[64], uint32_t da, uint32_t db, int scale_d) {
    asm volatile(
        "{\n.reg .pred p;\n.reg .b32 la, lb;\n.reg .b64 da, db;\nsetp.ne.b32 p, %66, 0;\n"
        "add.u32 la, %64, %67;\nadd.u32 lb, %65, %68;\n"
        "mov.b64 da, {la, 0x40000040};\nmov.b64 db, {lb, 0x40000040};\n"
        "wgmma.mma_async.sync.aligned.m64n128k16.f32.bf16.bf16 "
        "{%0, %1, %2, %3, %4, %5, %6, %7, %8, %9, %10, %11, %12, %13, %14, %15, %16, %17, %18, %19, %20, %21, %22, %23, %24, %25, %26, %27, %28, %29, %30, %31, %32, %33, %34, %35, %36, %37, %38, %39, %40, %41, %42, %43, %44, %45, %46, %47, %48, %49, %50, %51, %52, %53, %54, %55, %56, %57, %58, %59, %60, %61, %62, %63}, "
        "da, db, p, 1, 1, 0, 0;\n}\n"
        : "+f"(d[0]), "+f"(d[1]), "+f"(d[2]), "+f"(d[3]), "+f"(d[4]), "+f"(d[5]), "+f"(d[6]), "+f"(d[7]), "+f"(d[8]), "+f"(d[9]), "+f"(d[10]), "+f"(d[11]), "+f"(d[12]), "+f"(d[13]), "+f"(d[14]), "+f"(d[15]), "+f"(d[16]), "+f"(d[17]), "+f"(d[18]), "+f"(d[19]), "+f"(d[20]), "+f"(d[21]), "+f"(d[22]), "+f"(d[23]), "+f"(d[24]), "+f"(d[25]), "+f"(d[26]), "+f"(d[27]), "+f"(d[28]), "+f"(d[29]), "+f"(d[30]), "+f"(d[31]), "+f"(d[32]), "+f"(d[33]), "+f"(d[34]), "+f"(d[35]), "+f"(d[36]), "+f"(d[37]), "+f"(d[38]), "+f"(d[39]), "+f"(d[40]), "+f"(d[41]), "+f"(d[42]), "+f"(d[43]), "+f"(d[44]), "+f"(d[45]), "+f"(d[46]), "+f"(d[47]), "+f"(d[48]), "+f"(d[49]), "+f"(d[50]), "+f"(d[51]), "+f"(d[52]), "+f"(d[53]), "+f"(d[54]), "+f"(d[55]), "+f"(d[56]), "+f"(d[57]), "+f"(d[58]), "+f"(d[59]), "+f"(d[60]), "+f"(d[61]), "+f"(d[62]), "+f"(d[63])
        : "r"(da), "r"(db), "r"(scale_d), "n"(OA >> 4), "n"(OB >> 4));
}

template <int OB>
__device__ __forceinline__ void wgmma_rs_n128_tb(float (&d)[64], uint32_t a0, uint32_t a1, uint32_t a2, uint32_t a3, uint32_t db, int scale_d) {
    asm volatile(
        "{\n.reg .pred p;\n.reg .b32 lb;\n.reg .b64 db;\nsetp.ne.b32 p, %69, 0;\n"
        "add.u32 lb, %68, %70;\n"
        "mov.b64 db, {lb, 0x40000040};\n"
        "wgmma.mma_async.sync.aligned.m64n128k16.f32.bf16.bf16 "
        "{%0, %1, %2, %3, %4, %5, %6, %7, %8, %9, %10, %11, %12, %13, %14, %15, %16, %17, %18, %19, %20, %21, %22, %23, %24, %25, %26, %27, %28, %29, %30, %31, %32, %33, %34, %35, %36, %37, %38, %39, %40, %41, %42, %43, %44, %45, %46, %47, %48, %49, %50, %51, %52, %53, %54, %55, %56, %57, %58, %59, %60, %61, %62, %63}, "
        "{%64, %65, %66, %67}, db, p, 1, 1, 1;\n}\n"
        : "+f"(d[0]), "+f"(d[1]), "+f"(d[2]), "+f"(d[3]), "+f"(d[4]), "+f"(d[5]), "+f"(d[6]), "+f"(d[7]), "+f"(d[8]), "+f"(d[9]), "+f"(d[10]), "+f"(d[11]), "+f"(d[12]), "+f"(d[13]), "+f"(d[14]), "+f"(d[15]), "+f"(d[16]), "+f"(d[17]), "+f"(d[18]), "+f"(d[19]), "+f"(d[20]), "+f"(d[21]), "+f"(d[22]), "+f"(d[23]), "+f"(d[24]), "+f"(d[25]), "+f"(d[26]), "+f"(d[27]), "+f"(d[28]), "+f"(d[29]), "+f"(d[30]), "+f"(d[31]), "+f"(d[32]), "+f"(d[33]), "+f"(d[34]), "+f"(d[35]), "+f"(d[36]), "+f"(d[37]), "+f"(d[38]), "+f"(d[39]), "+f"(d[40]), "+f"(d[41]), "+f"(d[42]), "+f"(d[43]), "+f"(d[44]), "+f"(d[45]), "+f"(d[46]), "+f"(d[47]), "+f"(d[48]), "+f"(d[49]), "+f"(d[50]), "+f"(d[51]), "+f"(d[52]), "+f"(d[53]), "+f"(d[54]), "+f"(d[55]), "+f"(d[56]), "+f"(d[57]), "+f"(d[58]), "+f"(d[59]), "+f"(d[60]), "+f"(d[61]), "+f"(d[62]), "+f"(d[63])
        : "r"(a0), "r"(a1), "r"(a2), "r"(a3), "r"(db), "r"(scale_d), "n"(OB >> 4));
}

template <int OA, int OB>
__device__ __forceinline__ void wgmma_ss_n256_tb(float (&d)[128], uint32_t da, uint32_t db, int scale_d) {
    asm volatile(
        "{\n.reg .pred p;\n.reg .b32 la, lb;\n.reg .b64 da, db;\nsetp.ne.b32 p, %130, 0;\n"
        "add.u32 la, %128, %131;\nadd.u32 lb, %129, %132;\n"
        "mov.b64 da, {la, 0x40000040};\nmov.b64 db, {lb, 0x40000040};\n"
        "wgmma.mma_async.sync.aligned.m64n256k16.f32.bf16.bf16 "
        "{%0, %1, %2, %3, %4, %5, %6, %7, %8, %9, %10, %11, %12, %13, %14, %15, %16, %17, %18, %19, %20, %21, %22, %23, %24, %25, %26, %27, %28, %29, %30, %31, %32, %33, %34, %35, %36, %37, %38, %39, %40, %41, %42, %43, %44, %45, %46, %47, %48, %49, %50, %51, %52, %53, %54, %55, %56, %57, %58, %59, %60, %61, %62, %63, %64, %65, %66, %67, %68, %69, %70, %71, %72, %73, %74, %75, %76, %77, %78, %79, %80, %81, %82, %83, %84, %85, %86, %87, %88, %89, %90, %91, %92, %93, %94, %95, %96, %97, %98, %99, %100, %101, %102, %103, %104, %105, %106, %107, %108, %109, %110, %111, %112, %113, %114, %115, %116, %117, %118, %119, %120, %121, %122, %123, %124, %125, %126, %127}, "
        "da, db, p, 1, 1, 0, 1;\n}\n"
        : "+f"(d[0]), "+f"(d[1]), "+f"(d[2]), "+f"(d[3]), "+f"(d[4]), "+f"(d[5]), "+f"(d[6]), "+f"(d[7]), "+f"(d[8]), "+f"(d[9]), "+f"(d[10]), "+f"(d[11]), "+f"(d[12]), "+f"(d[13]), "+f"(d[14]), "+f"(d[15]), "+f"(d[16]), "+f"(d[17]), "+f"(d[18]), "+f"(d[19]), "+f"(d[20]), "+f"(d[21]), "+f"(d[22]), "+f"(d[23]), "+f"(d[24]), "+f"(d[25]), "+f"(d[26]), "+f"(d[27]), "+f"(d[28]), "+f"(d[29]), "+f"(d[30]), "+f"(d[31]), "+f"(d[32]), "+f"(d[33]), "+f"(d[34]), "+f"(d[35]), "+f"(d[36]), "+f"(d[37]), "+f"(d[38]), "+f"(d[39]), "+f"(d[40]), "+f"(d[41]), "+f"(d[42]), "+f"(d[43]), "+f"(d[44]), "+f"(d[45]), "+f"(d[46]), "+f"(d[47]), "+f"(d[48]), "+f"(d[49]), "+f"(d[50]), "+f"(d[51]), "+f"(d[52]), "+f"(d[53]), "+f"(d[54]), "+f"(d[55]), "+f"(d[56]), "+f"(d[57]), "+f"(d[58]), "+f"(d[59]), "+f"(d[60]), "+f"(d[61]), "+f"(d[62]), "+f"(d[63]), "+f"(d[64]), "+f"(d[65]), "+f"(d[66]), "+f"(d[67]), "+f"(d[68]), "+f"(d[69]), "+f"(d[70]), "+f"(d[71]), "+f"(d[72]), "+f"(d[73]), "+f"(d[74]), "+f"(d[75]), "+f"(d[76]), "+f"(d[77]), "+f"(d[78]), "+f"(d[79]), "+f"(d[80]), "+f"(d[81]), "+f"(d[82]), "+f"(d[83]), "+f"(d[84]), "+f"(d[85]), "+f"(d[86]), "+f"(d[87]), "+f"(d[88]), "+f"(d[89]), "+f"(d[90]), "+f"(d[91]), "+f"(d[92]), "+f"(d[93]), "+f"(d[94]), "+f"(d[95]), "+f"(d[96]), "+f"(d[97]), "+f"(d[98]), "+f"(d[99]), "+f"(d[100]), "+f"(d[101]), "+f"(d[102]), "+f"(d[103]), "+f"(d[104]), "+f"(d[105]), "+f"(d[106]), "+f"(d[107]), "+f"(d[108]), "+f"(d[109]), "+f"(d[110]), "+f"(d[111]), "+f"(d[112]), "+f"(d[113]), "+f"(d[114]), "+f"(d[115]), "+f"(d[116]), "+f"(d[117]), "+f"(d[118]), "+f"(d[119]), "+f"(d[120]), "+f"(d[121]), "+f"(d[122]), "+f"(d[123]), "+f"(d[124]), "+f"(d[125]), "+f"(d[126]), "+f"(d[127])
        : "r"(da), "r"(db), "r"(scale_d), "n"(OA >> 4), "n"(OB >> 4));
}

template <int OB>
__device__ __forceinline__ void wgmma_rs_n64_tb(float (&d)[32], uint32_t a0, uint32_t a1, uint32_t a2, uint32_t a3, uint32_t db, int scale_d) {
    asm volatile(
        "{\n.reg .pred p;\n.reg .b32 lb;\n.reg .b64 db;\nsetp.ne.b32 p, %37, 0;\n"
        "add.u32 lb, %36, %38;\n"
        "mov.b64 db, {lb, 0x40000040};\n"
        "wgmma.mma_async.sync.aligned.m64n64k16.f32.bf16.bf16 "
        "{%0, %1, %2, %3, %4, %5, %6, %7, %8, %9, %10, %11, %12, %13, %14, %15, %16, %17, %18, %19, %20, %21, %22, %23, %24, %25, %26, %27, %28, %29, %30, %31}, "
        "{%32, %33, %34, %35}, db, p, 1, 1, 1;\n}\n"
        : "+f"(d[0]), "+f"(d[1]), "+f"(d[2]), "+f"(d[3]), "+f"(d[4]), "+f"(d[5]), "+f"(d[6]), "+f"(d[7]), "+f"(d[8]), "+f"(d[9]), "+f"(d[10]), "+f"(d[11]), "+f"(d[12]), "+f"(d[13]), "+f"(d[14]), "+f"(d[15]), "+f"(d[16]), "+f"(d[17]), "+f"(d[18]), "+f"(d[19]), "+f"(d[20]), "+f"(d[21]), "+f"(d[22]), "+f"(d[23]), "+f"(d[24]), "+f"(d[25]), "+f"(d[26]), "+f"(d[27]), "+f"(d[28]), "+f"(d[29]), "+f"(d[30]), "+f"(d[31])
        : "r"(a0), "r"(a1), "r"(a2), "r"(a3), "r"(db), "r"(scale_d), "n"(OB >> 4));
}

template <int OA, int OB>
__device__ __forceinline__ void wgmma_ss_n64_tb(float (&d)[32], uint32_t da, uint32_t db, int scale_d) {
    asm volatile(
        "{\n.reg .pred p;\n.reg .b32 la, lb;\n.reg .b64 da, db;\nsetp.ne.b32 p, %34, 0;\n"
        "add.u32 la, %32, %35;\nadd.u32 lb, %33, %36;\n"
        "mov.b64 da, {la, 0x40000040};\nmov.b64 db, {lb, 0x40000040};\n"
        "wgmma.mma_async.sync.aligned.m64n64k16.f32.bf16.bf16 "
        "{%0, %1, %2, %3, %4, %5, %6, %7, %8, %9, %10, %11, %12, %13, %14, %15, %16, %17, %18, %19, %20, %21, %22, %23, %24, %25, %26, %27, %28, %29, %30, %31}, "
        "da, db, p, 1, 1, 0, 1;\n}\n"
        : "+f"(d[0]), "+f"(d[1]), "+f"(d[2]), "+f"(d[3]), "+f"(d[4]), "+f"(d[5]), "+f"(d[6]), "+f"(d[7]), "+f"(d[8]), "+f"(d[9]), "+f"(d[10]), "+f"(d[11]), "+f"(d[12]), "+f"(d[13]), "+f"(d[14]), "+f"(d[15]), "+f"(d[16]), "+f"(d[17]), "+f"(d[18]), "+f"(d[19]), "+f"(d[20]), "+f"(d[21]), "+f"(d[22]), "+f"(d[23]), "+f"(d[24]), "+f"(d[25]), "+f"(d[26]), "+f"(d[27]), "+f"(d[28]), "+f"(d[29]), "+f"(d[30]), "+f"(d[31])
        : "r"(da), "r"(db), "r"(scale_d), "n"(OA >> 4), "n"(OB >> 4));
}

#define SPLIT 4

struct Ring {
    uint32_t slot, phase;
    __device__ __forceinline__ void advance() {
        if (++slot == kSlots) { slot = 0; phase ^= 1; }
    }
};

constexpr float kScaleLog2e = 0.08838834764831845f * 1.4426950408889634f;

constexpr float kMaxSlack = 128.f;

struct SoftmaxTmp { float n0, n1, r0, r1; };

__device__ __forceinline__ void softmax_update_max(const float (&s)[64], float (&o)[64], float (&m)[2], float (&l)[2]) {
    constexpr float c = kScaleLog2e;
    float x0 = m[0], x1 = m[1];
#pragma unroll
    for (int j = 0; j < 16; j++) {
        x0 = fmaxf(x0, fmaxf(s[4 * j + 0], s[4 * j + 1]));
        x1 = fmaxf(x1, fmaxf(s[4 * j + 2], s[4 * j + 3]));
    }
    x0 = fmaxf(x0, __shfl_xor_sync(0xffffffffu, x0, 1));
    x1 = fmaxf(x1, __shfl_xor_sync(0xffffffffu, x1, 1));
    x0 = fmaxf(x0, __shfl_xor_sync(0xffffffffu, x0, 2));
    x1 = fmaxf(x1, __shfl_xor_sync(0xffffffffu, x1, 2));
    x0 = fmaxf(x0, -3.0e38f);
    x1 = fmaxf(x1, -3.0e38f);
    const float a0 = ex2((m[0] - x0) * c), a1 = ex2((m[1] - x1) * c);
    m[0] = x0;
    m[1] = x1;
    l[0] *= a0;
    l[1] *= a1;
#pragma unroll
    for (int j = 0; j < 16; j++) {
        o[4 * j + 0] *= a0;
        o[4 * j + 1] *= a0;
        o[4 * j + 2] *= a1;
        o[4 * j + 3] *= a1;
    }
}

__device__ __forceinline__ void softmax_head(const float (&s)[64], float (&o)[64], float (&m)[2], float (&l)[2], SoftmaxTmp& t) {
    auto I = [](float f) { return __float_as_int(f); };
    int x0 = max(I(s[0]), I(s[1])), x1 = max(I(s[2]), I(s[3])), y0 = max(I(s[4]), I(s[5])), y1 = max(I(s[6]), I(s[7]));
#pragma unroll
    for (int j = 2; j < 16; j += 2) {
        x0 = __vimax3_s32(x0, I(s[4 * j + 0]), I(s[4 * j + 1]));
        x1 = __vimax3_s32(x1, I(s[4 * j + 2]), I(s[4 * j + 3]));
        y0 = __vimax3_s32(y0, I(s[4 * j + 4]), I(s[4 * j + 5]));
        y1 = __vimax3_s32(y1, I(s[4 * j + 6]), I(s[4 * j + 7]));
    }
    const int lim0 = I(m[0] + kMaxSlack), lim1 = I(m[1] + kMaxSlack);
    const bool unsafe = __vimax3_s32(x0, y0, 0) > lim0 || __vimax3_s32(x1, y1, 0) > lim1;
    if (__builtin_expect(__any_sync(0xffffffffu, unsafe), 0)) softmax_update_max(s, o, m, l);
    t.n0 = -m[0] * kScaleLog2e;
    t.n1 = -m[1] * kScaleLog2e;
    t.r0 = l[0];
    t.r1 = l[1];
}
template <int J0, int J1>
__device__ __forceinline__ void softmax_exp(float (&s)[64], const SoftmaxTmp& t) {
    constexpr float c = kScaleLog2e;
#pragma unroll
    for (int j = J0; j < J1; j++) {
        s[4 * j + 0] = ex2(fmaf(s[4 * j + 0], c, t.n0));
        s[4 * j + 1] = ex2(fmaf(s[4 * j + 1], c, t.n0));
        s[4 * j + 2] = ex2(fmaf(s[4 * j + 2], c, t.n1));
        s[4 * j + 3] = ex2(fmaf(s[4 * j + 3], c, t.n1));
    }
}
__device__ __forceinline__ void softmax_pack(uint32_t (&p)[32], const float (&s)[64], float (&l)[2], SoftmaxTmp& t) {
#pragma unroll
    for (int j = 0; j < 16; j++) {
        t.r0 += s[4 * j + 0] + s[4 * j + 1];
        t.r1 += s[4 * j + 2] + s[4 * j + 3];
        p[2 * j + 0] = pack_bf16(s[4 * j + 0], s[4 * j + 1]);
        p[2 * j + 1] = pack_bf16(s[4 * j + 2], s[4 * j + 3]);
    }
    l[0] = t.r0;
    l[1] = t.r1;
}

template <int K> __device__ __forceinline__ void issue_qk_from(float (&s)[64], uint32_t dq, uint32_t dk) {
    if constexpr (K < 8) {
        wgmma_ss_n128<(K / 4) * 8192 + (K % 4) * 32, (K / 4) * 16384 + (K % 4) * 32>(s, dq, dk, K > 0);
        issue_qk_from<K + 1>(s, dq, dk);
    }
}
__device__ __forceinline__ void issue_qk(float (&s)[64], uint32_t dq, uint32_t dk) {
    issue_qk_from<0>(s, dq, dk);
    wg_commit();
}
template <int K> __device__ __forceinline__ void issue_pv_from(float (&o)[64], const uint32_t (&p)[32], uint32_t dv) {
    if constexpr (K < 8) {
        wgmma_rs_n128_tb<K * 2048>(o, p[4 * K], p[4 * K + 1], p[4 * K + 2], p[4 * K + 3], dv, 1);
        issue_pv_from<K + 1>(o, p, dv);
    }
}
__device__ __forceinline__ void issue_pv(float (&o)[64], const uint32_t (&p)[32], uint32_t dv) {
    issue_pv_from<0>(o, p, dv);
    wg_commit();
}

template <int K> __device__ __forceinline__ void issue_oproj_rs(float (&d)[32], const uint32_t (&a)[64], uint32_t db) {
    if constexpr (K < 16) {
        wgmma_rs_n64_tb<K * 2048>(d, a[4 * K], a[4 * K + 1], a[4 * K + 2], a[4 * K + 3], db, K > 0);
        issue_oproj_rs<K + 1>(d, a, db);
    }
}
template <int K> __device__ __forceinline__ void issue_oproj_ss(float (&d)[32], uint32_t da, uint32_t db) {
    if constexpr (K < 16) {
        wgmma_ss_n64_tb<(K / 4) * 8192 + (K % 4) * 32, K * 2048>(d, da, db, 1);
        issue_oproj_ss<K + 1>(d, da, db);
    }
}

__device__ __forceinline__ void store_head(uint32_t base, const uint32_t* p) {
    const int lane = threadIdx.x & 31, warp = (threadIdx.x >> 5) & 3;
    const int row = warp * 16 + (lane & 7) + ((lane >> 3) & 1) * 8;
    const uint32_t rb = base + row * 128;
#pragma unroll
    for (int k = 0; k < 8; k++) {
        const int chunk = (2 * k + (lane >> 4)) & 7;
        stmatrix_x4(rb + (k / 4) * 8192 + ((chunk ^ (row & 7)) << 4), p[4 * k], p[4 * k + 1], p[4 * k + 2], p[4 * k + 3]);
    }
}

__device__ __forceinline__ void finalize_head(uint32_t* p, const float (&o)[64], const float (&l)[2]) {
    float l0 = l[0], l1 = l[1];
    l0 += __shfl_xor_sync(0xffffffffu, l0, 1);
    l1 += __shfl_xor_sync(0xffffffffu, l1, 1);
    l0 += __shfl_xor_sync(0xffffffffu, l0, 2);
    l1 += __shfl_xor_sync(0xffffffffu, l1, 2);
    const float i0 = 1.0f / l0, i1 = 1.0f / l1;
#pragma unroll
    for (int j = 0; j < 16; j++) {
        p[2 * j + 0] = pack_bf16(o[4 * j + 0] * i0, o[4 * j + 1] * i0);
        p[2 * j + 1] = pack_bf16(o[4 * j + 2] * i1, o[4 * j + 3] * i1);
    }
}

enum : int { kBarTurn0 = 1, kBarTurn1 = 2, kBarAll = 3, kBarWg0 = 4, kBarWg1 = 5, kBarSums = 6 };
constexpr uint32_t kEmpty1 = 64, kEmptyV = 112, kFull3 = 128, kEmpty3 = 256;

struct Loader {
    const CUtensorMap* maps;
    uint32_t sb;
    __device__ __forceinline__ void wq(int t, uint32_t slot) const {
        const int cta = cta_id();
        const CUtensorMap* mp = maps + (cta >> 6) * 5;
        const uint32_t full = sb + kBarOff + 8 * slot;
        mbar_expect_tx(full, kSlotBytes + ((t & 1) ? 0u : 8192u));
        if (!(t & 1)) tma3d(sb + (t >> 1) * 8192, mp + 0, 0, (cta & 7) * kSq, t >> 1, full);
        tma3d(sb + kQBytes + slot * kSlotBytes, mp + 3, 0, t * 32, cta & 56, full);
    }
    __device__ __forceinline__ void kv(int t, uint32_t slot) const {
        const int cta = cta_id();
        const CUtensorMap* mp = maps + (cta >> 6) * 5;
        const uint32_t full = sb + kBarOff + 8 * slot;
        uint64_t pol;
        asm volatile("createpolicy.fractional.L2::evict_first.b64 %0, 1.0;" : "=l"(pol));
        mbar_expect_tx(full, kSlotBytes);
        tma3d_hint(sb + kQBytes + slot * kSlotBytes, mp + 1 + (t & 1), 0,
                   KVROW(((cta & 7) * kHkv + ((cta >> 3) & 7)) * kSk) + (t >> 1) * kTileN, 0, full, pol);
    }
    __device__ __forceinline__ void wo(int t, uint32_t slot) const {
        const int cta = cta_id();
        const CUtensorMap* mp = maps + (cta >> 6) * 5;
        const uint32_t full = sb + kBarOff + kFull3 + 8 * t;
        const int hkv = (cta >> 3) & 7;
        mbar_expect_tx(full, kSlotBytes);
        tma3d(sb + kQBytes + slot * kSlotBytes, mp + 4, 0, hkv * 512 + (((t >> 1) ^ t) & 1) * 256, (hkv + 1 + (t >> 1)) & 7, full);
    }
    __device__ __forceinline__ void kv_or_wo(int t, uint32_t slot) const {
        if (t < 2 * kKvTiles) kv(t, slot); else wo(t - 2 * kKvTiles, slot);
    }
};

__global__ void __launch_bounds__(kThreads, 1)
fused_gqa_kernel(const __grid_constant__ Params prm, __nv_bfloat16* __restrict__ out) {
    extern __shared__ __align__(1024) uint8_t smem_raw[];
    const uint32_t sb = smem_u32(smem_raw);
    const uint32_t sQ = sb, sRing = sb + kQBytes, sFull = sb + kBarOff, sEmpty1 = sFull + kEmpty1;
    const int warp8 = __shfl_sync(0xffffffffu, threadIdx.x >> 5, 0);
    const int wg = warp8 >> 2;
    const bool loader = warp8 == 4;
    const Loader ld{prm.maps, sb};

    if (loader && elect_one()) {
        for (int i = 0; i < kSlots; i++) {
            mbar_init(sFull + 8 * i, 1);
            mbar_init(sEmpty1 + 8 * i, 8);
        }
        mbar_init(sFull + kEmptyV, 8);
        for (int i = 0; i < kWTiles; i++) {
            mbar_init(sFull + kFull3 + 8 * i, 1);
            mbar_init(sFull + kEmpty3 + 8 * i, 4);
        }
        asm volatile("fence.mbarrier_init.release.cluster;" ::: "memory");
        fence_async_smem();
        for (int t = 0; t < kSlots; t++) ld.wq(t, t);
    }
    __syncthreads();

    const uint32_t sQw = sQ + wg * 32768;
    Ring r{0, 0};
    STAMP(0);

    {
        float acc[128];
        Ring prev{0, 0};
        auto release = [&](int t) {
            if (elect_one()) {
                mbar_arrive(sEmpty1 + 8 * prev.slot);
                if (loader) {
                    mbar_wait(sEmpty1 + 8 * prev.slot, prev.phase);
                    if (t + kSlots < kWTiles) ld.wq(t + kSlots, prev.slot); else ld.kv(t + kSlots - kWTiles, prev.slot);
                }
            }
            __syncwarp();
            prev.advance();
        };
#pragma unroll 1
        for (int t = 0; t < kWTiles; t++) {
            mbar_wait(sFull + 8 * r.slot, r.phase);
            if (t == 0) STAMP(1);
            const uint32_t da = mkdesc(sQ + (t >> 1) * 8192 + (t & 1) * 64, 16);
            const uint32_t db = mkdesc(sRing + r.slot * kSlotBytes + wg * 16384, 4096);
            wg_fence();
            wgmma_ss_n256_tb<0, 0>(acc, da, db, t > 0);
            wgmma_ss_n256_tb<32, 2048>(acc, da, db, 1);
            wg_commit();
            r.advance();
            wg_wait<1>();
            if (t > 0) release(t - 1);
        }
        wg_wait<0>();
        release(kWTiles - 1);
        reg_fence(acc);
        STAMP(2);
        uint32_t q[64];
#pragma unroll
        for (int i = 0; i < 64; i++) q[i] = pack_bf16(acc[2 * i], acc[2 * i + 1]);
        bar_sync(kBarAll, 256);
        store_head(sQw, q);
        store_head(sQw + 16384, q + 32);
        fence_async_smem();
        bar_sync_sel<kBarWg0, kBarWg1, 128>(wg);
    }
    STAMP(3);

    uint32_t op[64];
    uint32_t vslot = 0;
    {
        float oa[64], ob[64], s[64];
        uint32_t p[32];
        float ma[2] = {-INFINITY, -INFINITY}, mb[2] = {-INFINITY, -INFINITY};
        float la[2] = {0.f, 0.f}, lb[2] = {0.f, 0.f};
#pragma unroll
        for (int i = 0; i < 64; i++) { oa[i] = 0.f; ob[i] = 0.f; }
        const uint32_t dqa = mkdesc(sQw, 16), dqb = dqa + (16384 >> 4);
        const uint32_t dk0 = mkdesc(sRing, 16), dv0 = mkdesc(sRing, 16384);
        constexpr uint32_t kSlotDesc = kSlotBytes >> 4;
        SoftmaxTmp t;
        uint32_t opaque;
        asm volatile("mov.u32 %0, %%nsmid;" : "=r"(opaque));
        if (wg == 1) bar_arrive(kBarTurn0, 256);

        uint32_t kslot = r.slot;
        mbar_wait(sFull + 8 * r.slot, r.phase);
        r.advance();
        STAMP(4);
        bar_sync_sel<kBarTurn0, kBarTurn1, 256>(wg);
        STEP(0, 0);
        wg_fence();
        issue_qk(s, dqa, dk0 + kslot * kSlotDesc);
        bar_arrive_sel<kBarTurn1, kBarTurn0, 256>(wg);
        STEP(0, 1);
        wg_wait<0>();
        STEP(0, 2);
        reg_fence(s);
        softmax_head(s, oa, ma, la, t);
        softmax_exp<0, 16>(s, t);
        softmax_pack(p, s, la, t);

#pragma unroll 1
        for (int j = 0; j < kKvTiles; j++) {
            const uint32_t vprev = vslot;
            vslot = r.slot;
            reg_fence(oa);
            reg_fence(p);
            STEP(2 * j, 5);
            bar_sync_sel<kBarTurn0, kBarTurn1, 256>(wg);
            STEP(2 * j + 1, 0);
            wg_fence();
            issue_qk(s, dqb, dk0 + kslot * kSlotDesc);
            if (loader && j > 0 && elect_one()) ld.kv_or_wo(2 * j + 4, vprev);
            mbar_wait(sFull + 8 * r.slot, r.phase);
            r.advance();
            wg_fence();
            issue_pv(oa, p, dv0 + vslot * kSlotDesc);
            bar_arrive_sel<kBarTurn1, kBarTurn0, 256>(wg);
            STEP(2 * j + 1, 1);
            wg_wait<1>();
            STEP(2 * j + 1, 2);
            reg_fence(s);
            softmax_head(s, ob, mb, lb, t);
            softmax_exp<0, SPLIT>(s, t);
            reg_fence(s);
            STEP(2 * j + 1, 3);
            sched_break<4 * SPLIT>(opaque, s);
            wg_wait<0>();
            STEP(2 * j + 1, 4);
            reg_fence(oa);
            reg_fence(s);
            softmax_exp<SPLIT, 16>(s, t);
            softmax_pack(p, s, lb, t);
            if (j == kKvTiles - 1) break;

            const uint32_t kprev = kslot;
            kslot = r.slot;
            mbar_wait(sFull + 8 * r.slot, r.phase);
            r.advance();
            reg_fence(ob);
            reg_fence(p);
            STEP(2 * j + 1, 5);
            bar_sync_sel<kBarTurn0, kBarTurn1, 256>(wg);
            STEP(2 * j + 2, 0);
            wg_fence();
            issue_qk(s, dqa, dk0 + kslot * kSlotDesc);
            if (loader && elect_one()) ld.kv_or_wo(2 * j + 5, kprev);
            wg_fence();
            issue_pv(ob, p, dv0 + vslot * kSlotDesc);
            bar_arrive_sel<kBarTurn1, kBarTurn0, 256>(wg);
            STEP(2 * j + 2, 1);
            wg_wait<1>();
            STEP(2 * j + 2, 2);
            reg_fence(s);
            softmax_head(s, oa, ma, la, t);
            softmax_exp<0, SPLIT>(s, t);
            reg_fence(s);
            STEP(2 * j + 2, 3);
            sched_break<4 * SPLIT>(opaque, s);
            wg_wait<0>();
            STEP(2 * j + 2, 4);
            reg_fence(ob);
            reg_fence(s);
            softmax_exp<SPLIT, 16>(s, t);
            softmax_pack(p, s, la, t);
        }
        reg_fence(ob);
        reg_fence(p);
        bar_sync_sel<kBarTurn0, kBarTurn1, 256>(wg);
        wg_fence();
        issue_pv(ob, p, dv0 + vslot * kSlotDesc);
        if (loader && elect_one()) ld.wo(3, kslot);
        if (wg == 0) bar_arrive(kBarTurn1, 256);
        finalize_head(op, oa, la);
        store_head(sQw, op);
        wg_wait<0>();
        reg_fence(ob);
        if (elect_one()) {
            mbar_arrive(sFull + kEmptyV);
            if (loader) {
                mbar_wait(sFull + kEmptyV, 0);
                ld.wo(4, vslot);
            }
        }
        __syncwarp();
        finalize_head(op + 32, ob, lb);
        store_head(sQw + 16384, op + 32);
    }
    STAMP(5);

    {
        const int cta = cta_id();
        const int hkv = (cta >> 3) & 7, peers = cta & ~56;
        const int tid = threadIdx.x & 127;
        const uint32_t epoch = __ldcg(g_epoch + cta);
        fence_async_smem();
        bar_arrive_sel<kBarWg1, kBarWg0, 256>(wg);
        reg_fence(op);
        const uint32_t dA = mkdesc(sQ + (wg ^ 1) * 32768, 16);
        const bool refiller = (warp8 & 3) == 0;
        float acc[32], sum[32];
        uint32_t polls = 0;
#pragma unroll
        for (int i = 0; i < 32; i++) sum[i] = 0.f;
        const uint4* inbox = g_inbox + (size_t)cta * 8 * 4 * 128 + tid;

        auto release = [&](int t, uint32_t slot) {
            if (elect_one()) {
                mbar_arrive(sFull + kEmpty3 + 8 * t);
                if (refiller) {
                    mbar_wait(sFull + kEmpty3 + 8 * t, 0);
                    ld.wo(t + kSlots, slot);
                }
            }
            __syncwarp();
        };
        auto fetch = [&](uint4 (&v)[4], int k) {
            const uint4* src = inbox + ((hkv - k) & 7) * 512;
#pragma unroll
            for (int q = 0; q < 4; q++) v[q] = ld_packet(src + q * 128);
        };
        auto gather = [&](uint4 (&v)[4], int k) {
            const uint32_t tag = ~epoch & 1u;
            while ((((v[0].x ^ tag) | (v[1].x ^ tag) | (v[2].x ^ tag) | (v[3].x ^ tag)) & 1u) != 0 && polls < kPollLimit) {
                polls++;
                fetch(v, k);
            }
#pragma unroll
            for (int q = 0; q < 4; q++) {
                sum[8 * q + 0] += __uint_as_float((v[q].x << 16) & 0xfffe0000u);
                sum[8 * q + 1] += __uint_as_float(v[q].x & 0xffff0000u);
                sum[8 * q + 2] += __uint_as_float(v[q].y << 16);
                sum[8 * q + 3] += __uint_as_float(v[q].y & 0xffff0000u);
                sum[8 * q + 4] += __uint_as_float(v[q].z << 16);
                sum[8 * q + 5] += __uint_as_float(v[q].z & 0xffff0000u);
                sum[8 * q + 6] += __uint_as_float(v[q].w << 16);
                sum[8 * q + 7] += __uint_as_float(v[q].w & 0xffff0000u);
            }
        };

#pragma unroll
        for (int ps = 0; ps < 4; ps++) {
            const int t0 = 4 * ps + 2 * wg;
            const uint32_t slot0 = wg ? (5 + 4 * ps) % kSlots : (3 + 4 * ps) % kSlots;
            const uint32_t slot1 = wg ? (6 + 4 * ps) % kSlots : (4 + 4 * ps) % kSlots;
            uint4 va[4], vb[4];
            if (ps >= 2 && wg == 0) { fetch(va, 2 * ps - 3); fetch(vb, 2 * ps - 2); }
            mbar_wait(sFull + kFull3 + 8 * t0, 0);
            wg_fence();
            issue_oproj_rs<0>(acc, op, mkdesc(sRing + slot0 * kSlotBytes, 16));
            wg_commit();
            if (ps == 0) bar_sync_sel<kBarWg0, kBarWg1, 256>(wg);
            mbar_wait(sFull + kFull3 + 8 * (t0 + 1), 0);
            wg_fence();
            issue_oproj_ss<0>(acc, dA, mkdesc(sRing + slot1 * kSlotBytes, 16));
            wg_commit();
            if (ps >= 2 && wg == 0) { gather(va, 2 * ps - 3); gather(vb, 2 * ps - 2); }
            if (ps < 3) {
                wg_wait<1>();
                if (t0 + kSlots < kWTiles) release(t0, slot0);
            }
            wg_wait<0>();
            reg_fence(acc);
            if (ps < 3 && t0 + 1 + kSlots < kWTiles) release(t0 + 1, slot1);
            if (ps == 3) STAMP(6);
            if (ps < 3 || wg == 0) {
                const int dest = peers + (((hkv + 1 + 2 * ps + wg) & 7) << 3);
                uint4* dst = g_inbox + ((size_t)dest * 8 + hkv) * 512 + tid;
                const uint32_t tag = ~epoch & 1u;
#pragma unroll
                for (int q = 0; q < 4; q++) {
                    const uint32_t u = __float_as_uint(acc[8 * q]);
                    const uint32_t e0 = (((min(u & 0x7fffffffu, 0x7fc00000u) + 0x10000u) & 0x7ffe0000u) | (u & 0x80000000u)) >> 16;
                    const uint32_t w0 = (pack_bf16(0.f, acc[8 * q + 1]) & 0xffff0000u) | e0 | tag;
                    st_packet(dst + q * 128, w0, pack_bf16(acc[8 * q + 2], acc[8 * q + 3]), pack_bf16(acc[8 * q + 4], acc[8 * q + 5]),
                              pack_bf16(acc[8 * q + 6], acc[8 * q + 7]));
                }
            }
        }
        STAMP(7);

        const uint32_t sSum = sRing + tid * 16, sOut = sRing + kSlotBytes;
        if (wg == 0) {
            uint4 va[4], vb[4], vc[4];
            fetch(va, 5);
            fetch(vb, 6);
            fetch(vc, 7);
            bar_sync(kBarWg0, 128);
            gather(va, 5);
            gather(vb, 6);
            gather(vc, 7);
            if (polls >= kPollLimit) __trap();
#pragma unroll
            for (int q = 0; q < 8; q++)
                asm volatile("st.shared.v4.f32 [%0], {%1, %2, %3, %4};" ::"r"(sSum + q * 2048), "f"(sum[4 * q]), "f"(sum[4 * q + 1]),
                             "f"(sum[4 * q + 2]), "f"(sum[4 * q + 3]) : "memory");
            bar_arrive(kBarSums, 256);
            if (tid == 0) __stcg(g_epoch + cta, epoch + 1);
            STAMP(8);
        } else {
            bar_sync(kBarSums, 256);
            STAMP(8);
            uint32_t w[16];
#pragma unroll
            for (int q = 0; q < 8; q++) {
                float4 v;
                asm volatile("ld.shared.v4.f32 {%0, %1, %2, %3}, [%4];" : "=f"(v.x), "=f"(v.y), "=f"(v.z), "=f"(v.w) : "r"(sSum + q * 2048) : "memory");
                w[2 * q] = pack_bf16(acc[4 * q] + v.x, acc[4 * q + 1] + v.y);
                w[2 * q + 1] = pack_bf16(acc[4 * q + 2] + v.z, acc[4 * q + 3] + v.w);
            }
            const int lane = tid & 31, warp = tid >> 5;
            const int srow = warp * 16 + (lane & 7) + ((lane >> 3) & 1) * 8;
#pragma unroll
            for (int k = 0; k < 4; k++)
                stmatrix_x4(sOut + srow * 128 + (((2 * k + (lane >> 4)) ^ (srow & 7)) << 4), w[4 * k], w[4 * k + 1], w[4 * k + 2], w[4 * k + 3]);
            __syncwarp();
            __nv_bfloat16* dst = out + (size_t)((cta & 7) * kSq) * 1024 + (cta >> 6) * 512 + hkv * 64 + (lane & 7) * 8;
#pragma unroll
            for (int k = 0; k < 4; k++) {
                const int row = warp * 16 + k * 4 + (lane >> 3);
                uint4 v;
                asm volatile("ld.shared.v4.u32 {%0, %1, %2, %3}, [%4];" : "=r"(v.x), "=r"(v.y), "=r"(v.z), "=r"(v.w)
                             : "r"(sOut + row * 128 + (((lane & 7) ^ (row & 7)) << 4)) : "memory");
                *reinterpret_cast<uint4*>(dst + (size_t)row * 1024) = v;
            }
        }
    }
    STAMP(9);
}

typedef CUresult (*EncodeFn)(CUtensorMap*, CUtensorMapDataType, cuuint32_t, void*, const cuuint64_t*, const cuuint64_t*,
                             const cuuint32_t*, const cuuint32_t*, CUtensorMapInterleave, CUtensorMapSwizzle,
                             CUtensorMapL2promotion, CUtensorMapFloatOOBfill);

void encode_map(EncodeFn fn, CUtensorMap* m, void* ptr, uint64_t rows, uint64_t cols, uint32_t box_rows, uint32_t box_blocks) {
    cuuint64_t dims[3] = {64, rows, cols / 64};
    cuuint64_t strides[2] = {cols * 2, 128};
    cuuint32_t box[3] = {64, box_rows, box_blocks};
    cuuint32_t es[3] = {1, 1, 1};
    fn(m, CU_TENSOR_MAP_DATA_TYPE_BFLOAT16, 3, ptr, dims, strides, box, es, CU_TENSOR_MAP_INTERLEAVE_NONE,
       CU_TENSOR_MAP_SWIZZLE_128B, CU_TENSOR_MAP_L2_PROMOTION_L2_128B, CU_TENSOR_MAP_FLOAT_OOB_FILL_NONE);
}

}

extern "C" void kernel_launch(void* const* d_in, const int* in_sizes, int n_in, void* d_out, int out_size) {
    (void)in_sizes; (void)n_in; (void)out_size;
    static EncodeFn fn = nullptr;
    if (!fn) {
        cudaDriverEntryPointQueryResult qr;
        cudaGetDriverEntryPoint("cuTensorMapEncodeTiled", (void**)&fn, cudaEnableDefault, &qr);
        cudaFuncSetAttribute(fused_gqa_kernel, cudaFuncAttributeMaxDynamicSharedMemorySize, kSmemBytes);
    }
    Params prm;
    for (int br = 0; br < 2; br++) {
        void* const* in = d_in + br * 5;
        encode_map(fn, &prm.maps[br * 5 + 0], in[0], kB * kSq, kD, 64, 1);
        encode_map(fn, &prm.maps[br * 5 + 1], in[1], (uint64_t)kB * kHkv * kSk, kDh, kTileN, 2);
        encode_map(fn, &prm.maps[br * 5 + 2], in[2], (uint64_t)kB * kHkv * kSk, kDh, kTileN, 2);
        encode_map(fn, &prm.maps[br * 5 + 3], in[3], kD, kHq * kDh, 32, 8);
        encode_map(fn, &prm.maps[br * 5 + 4], in[4], kHq * kDh, kD, 256, 1);
    }
    fused_gqa_kernel<<<128, kThreads, kSmemBytes, cudaStreamPerThread>>>(prm, (__nv_bfloat16*)d_out);
}
```

```cpp
#include <cuda_runtime.h>
#include <cuda.h>
#include <cuda_bf16.h>
#include <stdint.h>

#define DESC64 1
namespace {

constexpr int kB = 8, kSq = 64, kD = 512, kHq = 32, kHkv = 8, kSk = 2048, kDh = 128;
constexpr int kTileN = 128;
constexpr int kKvTiles = kSk / kTileN;
constexpr int kSlots = 5;
constexpr uint32_t kSlotBytes = 32768;
constexpr uint32_t kQBytes = 65536;
constexpr uint32_t kBarOff = kQBytes + kSlots * kSlotBytes;
constexpr uint32_t kSmemBytes = kBarOff + 640 + 2176;
constexpr int kWTiles = 16;
constexpr int kThreads = 256;
constexpr uint32_t kSpinLimit = 1u << 24;
constexpr uint32_t kPollLimit = 1u << 20;

struct Params {
    CUtensorMap maps[10];
    const uint8_t* ptrs[10];
    uint4* inbox;
    __nv_bfloat16* out;
};

__device__ uint4 g_inbox[16 * 8 * 8 * 4 * 128];

#define KVROW(x) (x)
#define STAMP(i) do {} while (0)
#define STEP(step, i) do {} while (0)

__device__ __forceinline__ uint32_t smem_u32(const void* p) { return (uint32_t)__cvta_generic_to_shared(p); }
__device__ __forceinline__ void mbar_init(uint32_t a, uint32_t c) { asm volatile("mbarrier.init.shared::cta.b64 [%0], %1;" ::"r"(a), "r"(c) : "memory"); }
__device__ __forceinline__ void mbar_expect_tx(uint32_t a, uint32_t b) { asm volatile("mbarrier.arrive.expect_tx.shared::cta.b64 _, [%0], %1;" ::"r"(a), "r"(b) : "memory"); }
__device__ __forceinline__ void mbar_arrive(uint32_t a) { asm volatile("mbarrier.arrive.shared::cta.b64 _, [%0];" ::"r"(a) : "memory"); }
__device__ __forceinline__ bool mbar_test(uint32_t a, uint32_t parity) {
    uint32_t ok;
    asm volatile("{\n.reg .pred P;\nmbarrier.test_wait.parity.shared::cta.b64 P, [%1], %2;\nselp.b32 %0, 1, 0, P;\n}\n" : "=r"(ok) : "r"(a), "r"(parity) : "memory");
    return ok != 0;
}
__device__ __forceinline__ void mbar_wait(uint32_t a, uint32_t parity) {
    asm volatile(
        "{\n"
        ".reg .pred P;\n"
        ".reg .u32 n;\n"
        "mbarrier.try_wait.parity.shared::cta.b64 P, [%0], %1;\n"
        "@P bra DONE;\n"
        "mov.u32 n, 0;\n"
        "LOOP:\n"
        "mbarrier.try_wait.parity.shared::cta.b64 P, [%0], %1;\n"
        "@P bra DONE;\n"
        "add.u32 n, n, 1;\n"
        "setp.lt.u32 P, n, %2;\n"
        "@P bra LOOP;\n"
        "trap;\n"
        "DONE:\n"
        "}\n" ::"r"(a), "r"(parity), "n"(kSpinLimit) : "memory");
}
__device__ __forceinline__ void tma3d(uint32_t dst, const CUtensorMap* m, int c0, int c1, int c2, uint32_t bar) {
    asm volatile("cp.async.bulk.tensor.3d.shared::cluster.global.mbarrier::complete_tx::bytes [%0], [%1, {%3, %4, %5}], [%2];"
                 ::"r"(dst), "l"(m), "r"(bar), "r"(c0), "r"(c1), "r"(c2) : "memory");
}
__device__ __forceinline__ void tma3d_hint(uint32_t dst, const CUtensorMap* m, int c0, int c1, int c2, uint32_t bar, uint64_t pol) {
    asm volatile("cp.async.bulk.tensor.3d.shared::cluster.global.mbarrier::complete_tx::bytes.L2::cache_hint [%0], [%1, {%3, %4, %5}], [%2], %6;"
                 ::"r"(dst), "l"(m), "r"(bar), "r"(c0), "r"(c1), "r"(c2), "l"(pol) : "memory");
}
__device__ __forceinline__ void tma_refill(uint32_t enable, uint32_t dst, const CUtensorMap* m, int row, uint32_t bar) {
    asm volatile(
        "{\n.reg .pred p, q;\n.reg .b64 pol;\n"
        "elect.sync _|p, 0xffffffff;\n"
        "setp.ne.and.u32 q, %0, 0, p;\n"
        "createpolicy.fractional.L2::evict_first.b64 pol, 1.0;\n"
        "@q mbarrier.arrive.expect_tx.shared::cta.b64 _, [%4], 32768;\n"
        "@q cp.async.bulk.tensor.3d.shared::cluster.global.mbarrier::complete_tx::bytes.L2::cache_hint [%1], [%2, {0, %3, 0}], [%4], pol;\n"
        "}\n" ::"r"(enable), "r"(dst), "l"(m), "r"(row), "r"(bar) : "memory");
}
__device__ __forceinline__ void mbar_arrive_elect(uint32_t bar) {
    asm volatile("{\n.reg .pred p;\nelect.sync _|p, 0xffffffff;\n@p mbarrier.arrive.shared::cta.b64 _, [%0];\n}\n" ::"r"(bar) : "memory");
}
__device__ __forceinline__ void tma3d_elect(uint32_t dst, const CUtensorMap* m, int c1, int c2, uint32_t bar, uint32_t bytes) {
    asm volatile(
        "{\n.reg .pred p;\nelect.sync _|p, 0xffffffff;\n"
        "@p mbarrier.arrive.expect_tx.shared::cta.b64 _, [%4], %5;\n"
        "@p cp.async.bulk.tensor.3d.shared::cluster.global.mbarrier::complete_tx::bytes [%0], [%1, {0, %2, %3}], [%4];\n"
        "}\n" ::"r"(dst), "l"(m), "r"(c1), "r"(c2), "r"(bar), "r"(bytes) : "memory");
}
__device__ __forceinline__ void bulk_load_elect(uint32_t dst, const void* src, uint32_t bytes, uint32_t bar) {
    asm volatile(
        "{\n.reg .pred p;\nelect.sync _|p, 0xffffffff;\n"
        "@p mbarrier.arrive.expect_tx.shared::cta.b64 _, [%3], %2;\n"
        "@p cp.async.bulk.shared::cluster.global.mbarrier::complete_tx::bytes [%0], [%1], %2, [%3];\n"
        "}\n" ::"r"(dst), "l"(src), "r"(bytes), "r"(bar) : "memory");
}
__device__ __forceinline__ void st_flag_elect(uint32_t* p, uint32_t v) {
    asm volatile("{\n.reg .pred p;\nelect.sync _|p, 0xffffffff;\n@p st.relaxed.gpu.global.u32 [%0], %1;\n}\n" ::"l"(p), "r"(v) : "memory");
}
__device__ __forceinline__ void bulk_load(uint32_t dst, const void* src, uint32_t bytes, uint32_t bar) {
    asm volatile("cp.async.bulk.shared::cluster.global.mbarrier::complete_tx::bytes [%0], [%1], %2, [%3];"
                 ::"r"(dst), "l"(src), "r"(bytes), "r"(bar) : "memory");
}
__device__ __forceinline__ void prefetch_l2(const void* src, uint32_t bytes) {
    asm volatile("cp.async.bulk.prefetch.L2.global [%0], %1;" ::"l"(src), "r"(bytes) : "memory");
}
__device__ __forceinline__ void tma3d_prefetch(const CUtensorMap* m, int c0, int c1, int c2) {
    asm volatile("cp.async.bulk.prefetch.tensor.3d.L2.global [%0, {%1, %2, %3}];" ::"l"(m), "r"(c0), "r"(c1), "r"(c2) : "memory");
}
__device__ __forceinline__ void prefetch_line(const void* p) { asm volatile("prefetch.global.L2 [%0];" ::"l"(p) : "memory"); }
__device__ __forceinline__ void prefetch_map(const CUtensorMap* m) { asm volatile("prefetch.tensormap [%0];" ::"l"(m) : "memory"); }
__device__ __forceinline__ bool elect_one() {
    uint32_t p;
    asm volatile("{\n.reg .pred P;\nelect.sync _|P, 0xffffffff;\nselp.b32 %0, 1, 0, P;\n}\n" : "=r"(p));
    return p != 0;
}
__device__ __forceinline__ void bar_sync(int id, int n) { asm volatile("bar.sync %0, %1;" ::"r"(id), "r"(n) : "memory"); }
__device__ __forceinline__ void bar_arrive(int id, int n) { asm volatile("bar.arrive %0, %1;" ::"r"(id), "r"(n) : "memory"); }
template <int ID0, int ID1, int N> __device__ __forceinline__ void bar_sync_sel(int sel) {
    asm volatile("{\n.reg .pred P;\nsetp.eq.s32 P, %0, 0;\n@P bar.sync %1, %3;\n@!P bar.sync %2, %3;\n}\n" ::"r"(sel), "n"(ID0), "n"(ID1), "n"(N) : "memory");
}
template <int ID0, int ID1, int N> __device__ __forceinline__ void bar_arrive_sel(int sel) {
    asm volatile("{\n.reg .pred P;\nsetp.eq.s32 P, %0, 0;\n@P bar.arrive %1, %3;\n@!P bar.arrive %2, %3;\n}\n" ::"r"(sel), "n"(ID0), "n"(ID1), "n"(N) : "memory");
}
__device__ __forceinline__ int cta_id() {
    int v;
    asm volatile("mov.u32 %0, %%ctaid.x;" : "=r"(v));
    return v;
}
__device__ __forceinline__ void fence_async_smem() { asm volatile("fence.proxy.async.shared::cta;" ::: "memory"); }
__device__ __forceinline__ void wg_fence() { asm volatile("wgmma.fence.sync.aligned;" ::: "memory"); }
__device__ __forceinline__ void wg_commit() { asm volatile("wgmma.commit_group.sync.aligned;" ::: "memory"); }
template <int N> __device__ __forceinline__ void wg_wait() { asm volatile("wgmma.wait_group.sync.aligned %0;" ::"n"(N) : "memory"); }
template <int N> __device__ __forceinline__ void reg_fence(float (&r)[N]) {
#pragma unroll
    for (int i = 0; i < N; i++) asm volatile("" : "+f"(r[i])::"memory");
}
template <int N> __device__ __forceinline__ void reg_fence(uint32_t (&r)[N]) {
#pragma unroll
    for (int i = 0; i < N; i++) asm volatile("" : "+r"(r[i])::"memory");
}
typedef uint64_t desc_t;
__device__ __forceinline__ desc_t mkdesc(uint32_t addr, uint32_t lbo) { return 0x4000004000000000ull | ((addr >> 4) | ((lbo >> 4) << 16)); }
template <int N> __device__ __forceinline__ void sched_break(uint32_t never_all_ones, float (&s)[64]) {
    if (__builtin_expect(never_all_ones == 0xffffffffu, 0)) {
#pragma unroll
        for (int i = 0; i < N; i++) asm volatile("neg.f32 %0, %0;" : "+f"(s[i])::"memory");
    }
}
__device__ __forceinline__ uint32_t pack_bf16(float lo, float hi) {
    uint32_t r;
    asm("cvt.rn.bf16x2.f32 %0, %1, %2;" : "=r"(r) : "f"(hi), "f"(lo));
    return r;
}
__device__ __forceinline__ float ex2(float x) {
    float y;
    asm("ex2.approx.ftz.f32 %0, %1;" : "=f"(y) : "f"(x));
    return y;
}
#define ST_OP "st.relaxed.gpu.global.b128"
#define LD_OP "ld.relaxed.gpu.global.b128"
__device__ __forceinline__ void st_packet(uint4* dst, uint32_t a, uint32_t b, uint32_t c, uint32_t d) {
    asm volatile("{\n.reg .b64 lo, hi;\n.reg .b128 v;\nmov.b64 lo, {%1, %2};\nmov.b64 hi, {%3, %4};\nmov.b128 v, {lo, hi};\n"
                 ST_OP " [%0], v;\n}\n" ::"l"(dst), "r"(a), "r"(b), "r"(c), "r"(d) : "memory");
}
__device__ __forceinline__ uint4 ld_packet(const uint4* src) {
    uint4 r;
    asm volatile("{\n.reg .b64 lo, hi;\n.reg .b128 v;\n" LD_OP " v, [%4];\nmov.b128 {lo, hi}, v;\n"
                 "mov.b64 {%0, %1}, lo;\nmov.b64 {%2, %3}, hi;\n}\n" : "=r"(r.x), "=r"(r.y), "=r"(r.z), "=r"(r.w) : "l"(src) : "memory");
    return r;
}
__device__ __forceinline__ uint32_t ld_flag(const uint32_t* p) {
    uint32_t v;
    asm volatile("ld.relaxed.gpu.global.u32 %0, [%1];" : "=r"(v) : "l"(p) : "memory");
    return v;
}
__device__ __forceinline__ void ldmatrix_x4(uint32_t addr, uint32_t& a, uint32_t& b, uint32_t& c, uint32_t& d) {
    asm volatile("ldmatrix.sync.aligned.m8n8.x4.shared.b16 {%0, %1, %2, %3}, [%4];" : "=r"(a), "=r"(b), "=r"(c), "=r"(d) : "r"(addr) : "memory");
}
__device__ __forceinline__ void mma_16816(float* d, uint32_t a0, uint32_t a1, uint32_t a2, uint32_t a3, uint32_t b0, uint32_t b1) {
    asm volatile("mma.sync.aligned.m16n8k16.row.col.f32.bf16.bf16.f32 {%0, %1, %2, %3}, {%4, %5, %6, %7}, {%8, %9}, {%0, %1, %2, %3};"
                 : "+f"(d[0]), "+f"(d[1]), "+f"(d[2]), "+f"(d[3]) : "r"(a0), "r"(a1), "r"(a2), "r"(a3), "r"(b0), "r"(b1));
}
__device__ __forceinline__ void stmatrix_x4(uint32_t addr, uint32_t a, uint32_t b, uint32_t c, uint32_t d) {
    asm volatile("stmatrix.sync.aligned.m8n8.x4.shared.b16 [%0], {%1, %2, %3, %4};" ::"r"(addr), "r"(a), "r"(b), "r"(c), "r"(d) : "memory");
}

template <int OA, int OB>
__device__ __forceinline__ void wgmma_ss_n128(float (&d)[64], uint64_t da, uint64_t db, int scale_d) {
    asm volatile(
        "{\n.reg .pred p;\n.reg .b64 da, db;\nsetp.ne.b32 p, %66, 0;\n"
        "add.s64 da, %64, %67;\nadd.s64 db, %65, %68;\n"
        "wgmma.mma_async.sync.aligned.m64n128k16.f32.bf16.bf16 "
        "{%0, %1, %2, %3, %4, %5, %6, %7, %8, %9, %10, %11, %12, %13, %14, %15, %16, %17, %18, %19, %20, %21, %22, %23, %24, %25, %26, %27, %28, %29, %30, %31, %32, %33, %34, %35, %36, %37, %38, %39, %40, %41, %42, %43, %44, %45, %46, %47, %48, %49, %50, %51, %52, %53, %54, %55, %56, %57, %58, %59, %60, %61, %62, %63}, "
        "da, db, p, 1, 1, 0, 0;\n}\n"
        : "+f"(d[0]), "+f"(d[1]), "+f"(d[2]), "+f"(d[3]), "+f"(d[4]), "+f"(d[5]), "+f"(d[6]), "+f"(d[7]), "+f"(d[8]), "+f"(d[9]), "+f"(d[10]), "+f"(d[11]), "+f"(d[12]), "+f"(d[13]), "+f"(d[14]), "+f"(d[15]), "+f"(d[16]), "+f"(d[17]), "+f"(d[18]), "+f"(d[19]), "+f"(d[20]), "+f"(d[21]), "+f"(d[22]), "+f"(d[23]), "+f"(d[24]), "+f"(d[25]), "+f"(d[26]), "+f"(d[27]), "+f"(d[28]), "+f"(d[29]), "+f"(d[30]), "+f"(d[31]), "+f"(d[32]), "+f"(d[33]), "+f"(d[34]), "+f"(d[35]), "+f"(d[36]), "+f"(d[37]), "+f"(d[38]), "+f"(d[39]), "+f"(d[40]), "+f"(d[41]), "+f"(d[42]), "+f"(d[43]), "+f"(d[44]), "+f"(d[45]), "+f"(d[46]), "+f"(d[47]), "+f"(d[48]), "+f"(d[49]), "+f"(d[50]), "+f"(d[51]), "+f"(d[52]), "+f"(d[53]), "+f"(d[54]), "+f"(d[55]), "+f"(d[56]), "+f"(d[57]), "+f"(d[58]), "+f"(d[59]), "+f"(d[60]), "+f"(d[61]), "+f"(d[62]), "+f"(d[63])
        : "l"(da), "l"(db), "r"(scale_d), "n"(OA >> 4), "n"(OB >> 4));
}

template <int OB>
__device__ __forceinline__ void wgmma_rs_n128_tb(float (&d)[64], uint32_t a0, uint32_t a1, uint32_t a2, uint32_t a3, uint64_t db, int scale_d) {
    asm volatile(
        "{\n.reg .pred p;\n.reg .b64 db;\nsetp.ne.b32 p, %69, 0;\n"
        "add.s64 db, %68, %70;\n"
        "wgmma.mma_async.sync.aligned.m64n128k16.f32.bf16.bf16 "
        "{%0, %1, %2, %3, %4, %5, %6, %7, %8, %9, %10, %11, %12, %13, %14, %15, %16, %17, %18, %19, %20, %21, %22, %23, %24, %25, %26, %27, %28, %29, %30, %31, %32, %33, %34, %35, %36, %37, %38, %39, %40, %41, %42, %43, %44, %45, %46, %47, %48, %49, %50, %51, %52, %53, %54, %55, %56, %57, %58, %59, %60, %61, %62, %63}, "
        "{%64, %65, %66, %67}, db, p, 1, 1, 1;\n}\n"
        : "+f"(d[0]), "+f"(d[1]), "+f"(d[2]), "+f"(d[3]), "+f"(d[4]), "+f"(d[5]), "+f"(d[6]), "+f"(d[7]), "+f"(d[8]), "+f"(d[9]), "+f"(d[10]), "+f"(d[11]), "+f"(d[12]), "+f"(d[13]), "+f"(d[14]), "+f"(d[15]), "+f"(d[16]), "+f"(d[17]), "+f"(d[18]), "+f"(d[19]), "+f"(d[20]), "+f"(d[21]), "+f"(d[22]), "+f"(d[23]), "+f"(d[24]), "+f"(d[25]), "+f"(d[26]), "+f"(d[27]), "+f"(d[28]), "+f"(d[29]), "+f"(d[30]), "+f"(d[31]), "+f"(d[32]), "+f"(d[33]), "+f"(d[34]), "+f"(d[35]), "+f"(d[36]), "+f"(d[37]), "+f"(d[38]), "+f"(d[39]), "+f"(d[40]), "+f"(d[41]), "+f"(d[42]), "+f"(d[43]), "+f"(d[44]), "+f"(d[45]), "+f"(d[46]), "+f"(d[47]), "+f"(d[48]), "+f"(d[49]), "+f"(d[50]), "+f"(d[51]), "+f"(d[52]), "+f"(d[53]), "+f"(d[54]), "+f"(d[55]), "+f"(d[56]), "+f"(d[57]), "+f"(d[58]), "+f"(d[59]), "+f"(d[60]), "+f"(d[61]), "+f"(d[62]), "+f"(d[63])
        : "r"(a0), "r"(a1), "r"(a2), "r"(a3), "l"(db), "r"(scale_d), "n"(OB >> 4));
}

template <int OA, int OB>
__device__ __forceinline__ void wgmma_ss_n256_tb(float (&d)[128], uint64_t da, uint64_t db, int scale_d) {
    asm volatile(
        "{\n.reg .pred p;\n.reg .b64 da, db;\nsetp.ne.b32 p, %130, 0;\n"
        "add.s64 da, %128, %131;\nadd.s64 db, %129, %132;\n"
        "wgmma.mma_async.sync.aligned.m64n256k16.f32.bf16.bf16 "
        "{%0, %1, %2, %3, %4, %5, %6, %7, %8, %9, %10, %11, %12, %13, %14, %15, %16, %17, %18, %19, %20, %21, %22, %23, %24, %25, %26, %27, %28, %29, %30, %31, %32, %33, %34, %35, %36, %37, %38, %39, %40, %41, %42, %43, %44, %45, %46, %47, %48, %49, %50, %51, %52, %53, %54, %55, %56, %57, %58, %59, %60, %61, %62, %63, %64, %65, %66, %67, %68, %69, %70, %71, %72, %73, %74, %75, %76, %77, %78, %79, %80, %81, %82, %83, %84, %85, %86, %87, %88, %89, %90, %91, %92, %93, %94, %95, %96, %97, %98, %99, %100, %101, %102, %103, %104, %105, %106, %107, %108, %109, %110, %111, %112, %113, %114, %115, %116, %117, %118, %119, %120, %121, %122, %123, %124, %125, %126, %127}, "
        "da, db, p, 1, 1, 0, 1;\n}\n"
        : "+f"(d[0]), "+f"(d[1]), "+f"(d[2]), "+f"(d[3]), "+f"(d[4]), "+f"(d[5]), "+f"(d[6]), "+f"(d[7]), "+f"(d[8]), "+f"(d[9]), "+f"(d[10]), "+f"(d[11]), "+f"(d[12]), "+f"(d[13]), "+f"(d[14]), "+f"(d[15]), "+f"(d[16]), "+f"(d[17]), "+f"(d[18]), "+f"(d[19]), "+f"(d[20]), "+f"(d[21]), "+f"(d[22]), "+f"(d[23]), "+f"(d[24]), "+f"(d[25]), "+f"(d[26]), "+f"(d[27]), "+f"(d[28]), "+f"(d[29]), "+f"(d[30]), "+f"(d[31]), "+f"(d[32]), "+f"(d[33]), "+f"(d[34]), "+f"(d[35]), "+f"(d[36]), "+f"(d[37]), "+f"(d[38]), "+f"(d[39]), "+f"(d[40]), "+f"(d[41]), "+f"(d[42]), "+f"(d[43]), "+f"(d[44]), "+f"(d[45]), "+f"(d[46]), "+f"(d[47]), "+f"(d[48]), "+f"(d[49]), "+f"(d[50]), "+f"(d[51]), "+f"(d[52]), "+f"(d[53]), "+f"(d[54]), "+f"(d[55]), "+f"(d[56]), "+f"(d[57]), "+f"(d[58]), "+f"(d[59]), "+f"(d[60]), "+f"(d[61]), "+f"(d[62]), "+f"(d[63]), "+f"(d[64]), "+f"(d[65]), "+f"(d[66]), "+f"(d[67]), "+f"(d[68]), "+f"(d[69]), "+f"(d[70]), "+f"(d[71]), "+f"(d[72]), "+f"(d[73]), "+f"(d[74]), "+f"(d[75]), "+f"(d[76]), "+f"(d[77]), "+f"(d[78]), "+f"(d[79]), "+f"(d[80]), "+f"(d[81]), "+f"(d[82]), "+f"(d[83]), "+f"(d[84]), "+f"(d[85]), "+f"(d[86]), "+f"(d[87]), "+f"(d[88]), "+f"(d[89]), "+f"(d[90]), "+f"(d[91]), "+f"(d[92]), "+f"(d[93]), "+f"(d[94]), "+f"(d[95]), "+f"(d[96]), "+f"(d[97]), "+f"(d[98]), "+f"(d[99]), "+f"(d[100]), "+f"(d[101]), "+f"(d[102]), "+f"(d[103]), "+f"(d[104]), "+f"(d[105]), "+f"(d[106]), "+f"(d[107]), "+f"(d[108]), "+f"(d[109]), "+f"(d[110]), "+f"(d[111]), "+f"(d[112]), "+f"(d[113]), "+f"(d[114]), "+f"(d[115]), "+f"(d[116]), "+f"(d[117]), "+f"(d[118]), "+f"(d[119]), "+f"(d[120]), "+f"(d[121]), "+f"(d[122]), "+f"(d[123]), "+f"(d[124]), "+f"(d[125]), "+f"(d[126]), "+f"(d[127])
        : "l"(da), "l"(db), "r"(scale_d), "n"(OA >> 4), "n"(OB >> 4));
}

template <int OB>
__device__ __forceinline__ void wgmma_rs_n64_tb(float (&d)[32], uint32_t a0, uint32_t a1, uint32_t a2, uint32_t a3, uint64_t db, int scale_d) {
    asm volatile(
        "{\n.reg .pred p;\n.reg .b64 db;\nsetp.ne.b32 p, %37, 0;\n"
        "add.s64 db, %36, %38;\n"
        "wgmma.mma_async.sync.aligned.m64n64k16.f32.bf16.bf16 "
        "{%0, %1, %2, %3, %4, %5, %6, %7, %8, %9, %10, %11, %12, %13, %14, %15, %16, %17, %18, %19, %20, %21, %22, %23, %24, %25, %26, %27, %28, %29, %30, %31}, "
        "{%32, %33, %34, %35}, db, p, 1, 1, 1;\n}\n"
        : "+f"(d[0]), "+f"(d[1]), "+f"(d[2]), "+f"(d[3]), "+f"(d[4]), "+f"(d[5]), "+f"(d[6]), "+f"(d[7]), "+f"(d[8]), "+f"(d[9]), "+f"(d[10]), "+f"(d[11]), "+f"(d[12]), "+f"(d[13]), "+f"(d[14]), "+f"(d[15]), "+f"(d[16]), "+f"(d[17]), "+f"(d[18]), "+f"(d[19]), "+f"(d[20]), "+f"(d[21]), "+f"(d[22]), "+f"(d[23]), "+f"(d[24]), "+f"(d[25]), "+f"(d[26]), "+f"(d[27]), "+f"(d[28]), "+f"(d[29]), "+f"(d[30]), "+f"(d[31])
        : "r"(a0), "r"(a1), "r"(a2), "r"(a3), "l"(db), "r"(scale_d), "n"(OB >> 4));
}

template <int OA, int OB>
__device__ __forceinline__ void wgmma_ss_n64_tb(float (&d)[32], uint64_t da, uint64_t db, int scale_d) {
    asm volatile(
        "{\n.reg .pred p;\n.reg .b64 da, db;\nsetp.ne.b32 p, %34, 0;\n"
        "add.s64 da, %32, %35;\nadd.s64 db, %33, %36;\n"
        "wgmma.mma_async.sync.aligned.m64n64k16.f32.bf16.bf16 "
        "{%0, %1, %2, %3, %4, %5, %6, %7, %8, %9, %10, %11, %12, %13, %14, %15, %16, %17, %18, %19, %20, %21, %22, %23, %24, %25, %26, %27, %28, %29, %30, %31}, "
        "da, db, p, 1, 1, 0, 1;\n}\n"
        : "+f"(d[0]), "+f"(d[1]), "+f"(d[2]), "+f"(d[3]), "+f"(d[4]), "+f"(d[5]), "+f"(d[6]), "+f"(d[7]), "+f"(d[8]), "+f"(d[9]), "+f"(d[10]), "+f"(d[11]), "+f"(d[12]), "+f"(d[13]), "+f"(d[14]), "+f"(d[15]), "+f"(d[16]), "+f"(d[17]), "+f"(d[18]), "+f"(d[19]), "+f"(d[20]), "+f"(d[21]), "+f"(d[22]), "+f"(d[23]), "+f"(d[24]), "+f"(d[25]), "+f"(d[26]), "+f"(d[27]), "+f"(d[28]), "+f"(d[29]), "+f"(d[30]), "+f"(d[31])
        : "l"(da), "l"(db), "r"(scale_d), "n"(OA >> 4), "n"(OB >> 4));
}

#define PF_W 3
#define PF_KV 1
#define PF_KV_AT 2
#define PF_WO_AT 99
#define PF_MAP 0
#define QLEAD 0
#define OPP 1
#define FENCE_MODE 1
#define INIT_FENCE() asm volatile("fence.mbarrier_init.release.cluster;" ::: "memory")
#define OSTEP(a, b) do {} while (0)
#define ALLRS 1
#define NOFETCH 1
#define NOSEND 0
#define PF_N0 0
#define PF_N1 8
#define PF_A 1
#define PF_B 2
#define PF_MAX 24
#define PF_WD 1
#define PF_X 1
#define LATEK 7
#define LIGHTPOLL 0
#define PF_WO_S0 99
#define PF_WO_U 2
#define PF_WO_T0 5
#define FETCH_MODE 0
#define WARM_WO 1
#define PREWRITE 0
#define PACE 0
#define PVSPLIT 7
#define KTEST 2
#define FASTLOAD 1
#define FIRSTFAST 1
#define PF_WO_END 2
#define PROBE_K 0
#define PROBE_AT 9
#define BULK_AT 1
#define FLAG7 1
#define SENDBAR 1
#define PF_ENTRY 2
#define PF_ENTRY_X 1
#define KV_EAGER 2
#define PACE_TAU 0
#define PACE_T0 0
#define QSTEP(a, b) do {} while (0)
#define PF_TAB 0x2222222211111111ull
#define COLLECT_AT 0
#define ALLIN 1
#define SENDFIRST 0
#define V1_AT 0
#define SKIPREL 1
#define SPLIT 4

struct Ring {
    uint32_t slot, phase;
    __device__ __forceinline__ void advance() {
        if (++slot == kSlots) slot = 0;
        if (slot == kWTiles % kSlots) phase ^= 1;
    }
};

constexpr float kScaleLog2e = 0.08838834764831845f * 1.4426950408889634f;

constexpr float kMaxSlack = 128.f;

struct SoftmaxTmp { float n0, n1, r0, r1; };

__device__ __forceinline__ void softmax_update_max(bool first, const float (&s)[64], float (&o)[64], float (&m)[2], float (&l)[2]) {
    constexpr float c = kScaleLog2e;
    float x0 = m[0], x1 = m[1];
#pragma unroll
    for (int j = 0; j < 16; j++) {
        x0 = fmaxf(x0, fmaxf(s[4 * j + 0], s[4 * j + 1]));
        x1 = fmaxf(x1, fmaxf(s[4 * j + 2], s[4 * j + 3]));
    }
    x0 = fmaxf(x0, __shfl_xor_sync(0xffffffffu, x0, 1));
    x1 = fmaxf(x1, __shfl_xor_sync(0xffffffffu, x1, 1));
    x0 = fmaxf(x0, __shfl_xor_sync(0xffffffffu, x0, 2));
    x1 = fmaxf(x1, __shfl_xor_sync(0xffffffffu, x1, 2));
    x0 = fmaxf(x0, -3.0e38f);
    x1 = fmaxf(x1, -3.0e38f);
    if (!first) {
        const float a0 = ex2((m[0] - x0) * c), a1 = ex2((m[1] - x1) * c);
        l[0] *= a0;
        l[1] *= a1;
#pragma unroll
        for (int j = 0; j < 16; j++) {
            o[4 * j + 0] *= a0;
            o[4 * j + 1] *= a0;
            o[4 * j + 2] *= a1;
            o[4 * j + 3] *= a1;
        }
    }
    m[0] = x0;
    m[1] = x1;
}

__device__ __forceinline__ bool softmax_check(const float (&s)[64], const float (&m)[2]) {
    auto I = [](float f) { return __float_as_int(f); };
    int x0 = max(I(s[0]), I(s[1])), x1 = max(I(s[2]), I(s[3])), y0 = max(I(s[4]), I(s[5])), y1 = max(I(s[6]), I(s[7]));
#pragma unroll
    for (int j = 2; j < 16; j += 2) {
        x0 = __vimax3_s32(x0, I(s[4 * j + 0]), I(s[4 * j + 1]));
        x1 = __vimax3_s32(x1, I(s[4 * j + 2]), I(s[4 * j + 3]));
        y0 = __vimax3_s32(y0, I(s[4 * j + 4]), I(s[4 * j + 5]));
        y1 = __vimax3_s32(y1, I(s[4 * j + 6]), I(s[4 * j + 7]));
    }
    const int lim0 = I(m[0] + kMaxSlack), lim1 = I(m[1] + kMaxSlack);
    return __vimax3_s32(x0, y0, 0) > lim0 || __vimax3_s32(x1, y1, 0) > lim1;
}
__device__ __forceinline__ void softmax_ref(bool unsafe, bool first, const float (&s)[64], float (&o)[64], float (&m)[2], float (&l)[2], SoftmaxTmp& t) {
    if (__builtin_expect(__any_sync(0xffffffffu, unsafe), 0)) softmax_update_max(first, s, o, m, l);
    t.n0 = -m[0] * kScaleLog2e;
    t.n1 = -m[1] * kScaleLog2e;
    t.r0 = l[0];
    t.r1 = l[1];
}
__device__ __forceinline__ void softmax_head(bool first, const float (&s)[64], float (&o)[64], float (&m)[2], float (&l)[2], SoftmaxTmp& t) {
    softmax_ref(softmax_check(s, m), first, s, o, m, l, t);
}
template <int J0, int J1>
__device__ __forceinline__ void softmax_exp(float (&s)[64], const SoftmaxTmp& t) {
    constexpr float c = kScaleLog2e;
#pragma unroll
    for (int j = J0; j < J1; j++) {
        s[4 * j + 0] = ex2(fmaf(s[4 * j + 0], c, t.n0));
        s[4 * j + 1] = ex2(fmaf(s[4 * j + 1], c, t.n0));
        s[4 * j + 2] = ex2(fmaf(s[4 * j + 2], c, t.n1));
        s[4 * j + 3] = ex2(fmaf(s[4 * j + 3], c, t.n1));
    }
}
__device__ __forceinline__ void softmax_pack(uint32_t (&p)[32], const float (&s)[64], float (&l)[2], SoftmaxTmp& t) {
#pragma unroll
    for (int j = 0; j < 16; j++) {
        t.r0 += s[4 * j + 0] + s[4 * j + 1];
        t.r1 += s[4 * j + 2] + s[4 * j + 3];
        p[2 * j + 0] = pack_bf16(s[4 * j + 0], s[4 * j + 1]);
        p[2 * j + 1] = pack_bf16(s[4 * j + 2], s[4 * j + 3]);
    }
    l[0] = t.r0;
    l[1] = t.r1;
}

template <int K> __device__ __forceinline__ void issue_qk_from(float (&s)[64], desc_t dq, desc_t dk) {
    if constexpr (K < 8) {
        wgmma_ss_n128<(K / 4) * 8192 + (K % 4) * 32, (K / 4) * 16384 + (K % 4) * 32>(s, dq, dk, K > 0);
        issue_qk_from<K + 1>(s, dq, dk);
    }
}
__device__ __forceinline__ void issue_qk(float (&s)[64], desc_t dq, desc_t dk) {
    issue_qk_from<0>(s, dq, dk);
    wg_commit();
}
template <int K, int END = 8> __device__ __forceinline__ void issue_pv_from(float (&o)[64], const uint32_t (&p)[32], desc_t dv) {
    if constexpr (K < END) {
        wgmma_rs_n128_tb<K * 2048>(o, p[4 * K], p[4 * K + 1], p[4 * K + 2], p[4 * K + 3], dv, 1);
        issue_pv_from<K + 1, END>(o, p, dv);
    }
}
__device__ __forceinline__ void issue_pv(float (&o)[64], const uint32_t (&p)[32], desc_t dv) {
    issue_pv_from<0>(o, p, dv);
    wg_commit();
}

template <int K, bool FIRST> __device__ __forceinline__ void issue_oproj_rs(float (&d)[32], const uint32_t (&a)[64], desc_t db) {
    if constexpr (K < 16) {
        wgmma_rs_n64_tb<K * 2048>(d, a[4 * K], a[4 * K + 1], a[4 * K + 2], a[4 * K + 3], db, !FIRST || K > 0);
        issue_oproj_rs<K + 1, FIRST>(d, a, db);
    }
}
template <int K> __device__ __forceinline__ void issue_oproj_ss(float (&d)[32], desc_t da, desc_t db) {
    if constexpr (K < 16) {
        wgmma_ss_n64_tb<(K / 4) * 8192 + (K % 4) * 32, K * 2048>(d, da, db, 1);
        issue_oproj_ss<K + 1>(d, da, db);
    }
}

__device__ __forceinline__ void store_head(uint32_t base, const uint32_t* p) {
    const int lane = threadIdx.x & 31, warp = (threadIdx.x >> 5) & 3;
    const int row = warp * 16 + (lane & 7) + ((lane >> 3) & 1) * 8;
    const uint32_t rb = base + row * 128;
#pragma unroll
    for (int k = 0; k < 8; k++) {
        const int chunk = (2 * k + (lane >> 4)) & 7;
        stmatrix_x4(rb + (k / 4) * 8192 + ((chunk ^ (row & 7)) << 4), p[4 * k], p[4 * k + 1], p[4 * k + 2], p[4 * k + 3]);
    }
}

__device__ __forceinline__ void load_head(uint32_t base, uint32_t* p) {
    const int lane = threadIdx.x & 31, warp = (threadIdx.x >> 5) & 3;
    const int row = warp * 16 + (lane & 7) + ((lane >> 3) & 1) * 8;
    const uint32_t rb = base + row * 128;
#pragma unroll
    for (int k = 0; k < 8; k++) {
        const int chunk = (2 * k + (lane >> 4)) & 7;
        ldmatrix_x4(rb + (k / 4) * 8192 + ((chunk ^ (row & 7)) << 4), p[4 * k], p[4 * k + 1], p[4 * k + 2], p[4 * k + 3]);
    }
}

__device__ __forceinline__ void finalize_head(uint32_t* p, const float (&o)[64], const float (&l)[2]) {
    float l0 = l[0], l1 = l[1];
    l0 += __shfl_xor_sync(0xffffffffu, l0, 1);
    l1 += __shfl_xor_sync(0xffffffffu, l1, 1);
    l0 += __shfl_xor_sync(0xffffffffu, l0, 2);
    l1 += __shfl_xor_sync(0xffffffffu, l1, 2);
    const float i0 = 1.0f / l0, i1 = 1.0f / l1;
#pragma unroll
    for (int j = 0; j < 16; j++) {
        p[2 * j + 0] = pack_bf16(o[4 * j + 0] * i0, o[4 * j + 1] * i0);
        p[2 * j + 1] = pack_bf16(o[4 * j + 2] * i1, o[4 * j + 3] * i1);
    }
}

enum : int { kBarTurn0 = 1, kBarTurn1 = 2, kBarAll = 3, kBarWg0 = 4, kBarWg1 = 5, kBarSums = 6 };
constexpr uint32_t kEmptyV = 40, kEpoch = 48, kBulk = 64, kFull1 = 128, kFull3 = 256, kEmpty1 = 384, kEmpty3 = 512;

constexpr int kQLead = QLEAD;
__host__ __device__ constexpr int wq_owner(int t) { return t < kQLead ? 0 : (t >= kWTiles - kQLead ? 1 : ((t - kQLead) & 1)); }
__host__ __device__ constexpr int wq_chunk(int t) {
    return t < kQLead ? t : (t >= kWTiles - kQLead ? t - 8 : (((t - kQLead) & 1) ? (t - kQLead) >> 1 : kQLead + ((t - kQLead) >> 1)));
}
__host__ __device__ constexpr int wq_tile(int w, int kc) {
    return w == 0 ? (kc < kQLead ? kc : kQLead + 2 * (kc - kQLead)) : (kc >= 8 - kQLead ? kc + 8 : kQLead + 2 * kc + 1);
}

__host__ __device__ constexpr uint64_t pf_prefix(int first) {
    uint64_t r = 0;
    int acc = 0;
    for (int n = 0; n < 16; n++) {
        if (n >= first && n < first + 8) r |= (uint64_t)acc << (8 * (n - first));
        acc += (int)((PF_TAB >> (4 * n)) & 15);
    }
    return r;
}
constexpr uint64_t kPfLo = pf_prefix(0), kPfHi = pf_prefix(8);

struct Loader {
    const CUtensorMap* maps;
    uint32_t sb;
    __device__ __forceinline__ void wq(int t, uint32_t slot) const {
        const int cta = cta_id();
        const CUtensorMap* mp = maps + (cta >> 6) * 5;
        const uint32_t full = sb + kBarOff + kFull1 + 8 * t;
        const int w = wq_owner(t), kc = wq_chunk(t);
        mbar_expect_tx(full, kSlotBytes + (w ? 0u : 8192u));
        if (!w) tma3d(sb + kc * 8192, mp + 0, 0, (cta & 7) * kSq, kc, full);
        tma3d(sb + kQBytes + slot * kSlotBytes, mp + 3, 0, kc * 64, (cta & 56) + w * 4, full);
    }
    __device__ __forceinline__ void wq_prefetch(int t) const {
        const int cta = cta_id();
        tma3d_prefetch(maps + (cta >> 6) * 5 + 3, 0, wq_chunk(t) * 64, (cta & 56) + wq_owner(t) * 4);
    }
    __device__ __forceinline__ void wq_share(const uint8_t* const* ptrs, int t) const {
        const int cta = cta_id(), lane = threadIdx.x & 31;
        prefetch_line(ptrs[(cta >> 6) * 5 + 3] + (size_t)(wq_chunk(t) * 64 + (cta & 7) * 8 + (lane >> 2)) * 8192 + (cta & 56) * 128 +
                      wq_owner(t) * 512 + (lane & 3) * 128);
    }
    __device__ __forceinline__ void kv(int t, uint32_t slot) const {
        const int cta = cta_id();
        const CUtensorMap* mp = maps + (cta >> 6) * 5;
        const uint32_t full = sb + kBarOff + 8 * slot;
        uint64_t pol;
        asm volatile("createpolicy.fractional.L2::evict_first.b64 %0, 1.0;" : "=l"(pol));
        mbar_expect_tx(full, kSlotBytes);
        tma3d_hint(sb + kQBytes + slot * kSlotBytes, mp + 1 + (t & 1), 0,
                   KVROW(((cta & 7) * kHkv + ((cta >> 3) & 7)) * kSk) + (t >> 1) * kTileN, 0, full, pol);
    }
    __device__ __forceinline__ void wo(int t, uint32_t slot) const {
        const int cta = cta_id();
        const CUtensorMap* mp = maps + (cta >> 6) * 5;
        const uint32_t full = sb + kBarOff + kFull3 + 8 * t;
        const int hkv = (cta >> 3) & 7;
        mbar_expect_tx(full, kSlotBytes);
        tma3d(sb + kQBytes + slot * kSlotBytes, mp + 4, 0, hkv * 512 + (((t >> 1) ^ t) & 1) * 256, (hkv + 1 + (t >> 1)) & 7, full);
    }
    __device__ __forceinline__ void wo_share(const uint8_t* const* ptrs, int step, int warp8) const {
        const int t = PF_WO_T0 + ((step - PF_WO_S0) * 2 + (warp8 >> 2)) * PF_WO_U + (warp8 & 3);
        if ((warp8 & 3) < PF_WO_U && t < kWTiles) {
            const int cta = cta_id(), hkv = (cta >> 3) & 7;
            prefetch_line(ptrs[(cta >> 6) * 5 + 4] +
                          (size_t)(hkv * 512 + (((t >> 1) ^ t) & 1) * 256 + (cta & 7) * 32 + (threadIdx.x & 31)) * 1024 +
                          ((hkv + 1 + (t >> 1)) & 7) * 128);
        }
    }
    __device__ __forceinline__ void wo_tile_share(const uint8_t* const* ptrs, int t) const {
        const int cta = cta_id(), hkv = (cta >> 3) & 7;
        prefetch_line(ptrs[(cta >> 6) * 5 + 4] +
                      (size_t)(hkv * 512 + (((t >> 1) ^ t) & 1) * 256 + (cta & 7) * 32 + (threadIdx.x & 31)) * 1024 +
                      ((hkv + 1 + (t >> 1)) & 7) * 128);
    }
    __device__ __forceinline__ void kv_or_wo(int t, uint32_t slot) const {
        if (t < 2 * kKvTiles) kv(t, slot); else wo(t - 2 * kKvTiles, slot);
    }
};

__global__ void __launch_bounds__(kThreads, 1)
fused_gqa_kernel(const __grid_constant__ Params prm) {
    extern __shared__ __align__(1024) uint8_t smem_raw[];
    const uint32_t sb = smem_u32(smem_raw);
    STAMP(15);
    const uint32_t sQ = sb, sRing = sb + kQBytes, sFull = sb + kBarOff;
    const int warp8 = __shfl_sync(0xffffffffu, threadIdx.x >> 5, 0);
    const int wg = warp8 >> 2;
    const bool loader = warp8 == 4;
    const Loader ld{prm.maps, sb};

    if (PF_W == 2 && wg == 0) {
        const int cta = blockIdx.x, tid = threadIdx.x;
        const uint8_t* w = prm.ptrs[(cta >> 6) * 5 + 3] + (size_t)((tid >> 3) * 8 + (cta & 7)) * 8192 + (cta & 56) * 128 + (tid & 7) * 128;
        if (tid < 64) prefetch_line(prm.ptrs[(cta >> 6) * 5] + (size_t)((cta & 7) * 64 + (cta & 56)) * 1024 + tid * 128);
#pragma unroll
        for (int i = 0; i < 4; i++) prefetch_line(w + (size_t)i * 128 * 8192);
    }
    if (PF_ENTRY > 0 && warp8 < PF_ENTRY) ld.wq_share(prm.ptrs, warp8);
    if (PF_ENTRY_X && (warp8 == 6 || warp8 == 7)) {
        const int cta = blockIdx.x;
        prefetch_line(prm.ptrs[(cta >> 6) * 5] + (size_t)((cta & 7) * 64 + (cta & 56)) * 1024 + (threadIdx.x - 192) * 128);
    }
    if (PF_MAP && warp8 == 5 && (threadIdx.x & 31) < 5) prefetch_map(prm.maps + (blockIdx.x >> 6) * 5 + (threadIdx.x & 31));
    if (elect_one()) {
        if (loader) {
#pragma unroll
            for (int t = 0; t < kSlots; t++) mbar_init(sFull + kFull1 + 8 * t, 1);
            INIT_FENCE();
            STAMP(13);
#pragma unroll
            for (int t = 0; t < kSlots; t++) ld.wq(t, t);
            STAMP(14);
            if (PF_W == 1) {
                const int b = cta_id() & 7;
                ld.wq_prefetch(kSlots + b);
                if (b < kWTiles - kSlots - 8) ld.wq_prefetch(kSlots + 8 + b);
            }
        } else if (warp8 < 4) {
#pragma unroll
            for (int i = 0; i < 8; i++) mbar_init(sFull + kEmpty1 + 64 * warp8 + 8 * i, 4);
            INIT_FENCE();
        } else if (warp8 == 5) {
#pragma unroll
            for (int i = kSlots; i < kWTiles; i++) mbar_init(sFull + kFull1 + 8 * i, 1);
#pragma unroll
            for (int i = 0; i < 3; i++) mbar_init(sFull + kBulk + 8 * i, 1);

            INIT_FENCE();
        } else {
#pragma unroll
            for (int i = 0; i < 8; i++) mbar_init(sFull + kFull3 + 64 * (warp8 - 6) + 8 * i, 1);
#pragma unroll
            for (int i = 0; i < 3; i++) mbar_init(sFull + 24 * (warp8 - 6) + 8 * i, warp8 == 7 && i == 2 ? 8 : 1);
            INIT_FENCE();
        }
    }
    __syncthreads();
    if (PF_W == 3) {
        if (warp8 < PF_WD) ld.wq_share(prm.ptrs, kSlots + warp8);
        if (PF_X && !PF_ENTRY_X && (warp8 == 6 || warp8 == 7)) {
            const int cta = blockIdx.x;
            prefetch_line(prm.ptrs[(cta >> 6) * 5] + (size_t)((cta & 7) * 64 + (cta & 56)) * 1024 + (threadIdx.x - 192) * 128);
        }
    }

    uint32_t epoch0 = 0;
    if (threadIdx.x == 160) {
        const int cta = blockIdx.x, hkv = (cta >> 3) & 7;
        if (WARM_WO) prefetch_line(prm.ptrs[(cta >> 6) * 5 + 4] + (size_t)(hkv * 512 + (cta & 7) * 64) * 1024);
        epoch0 = __ldcg(reinterpret_cast<const uint32_t*>(prm.inbox + (size_t)((cta >> 6) * 8 + (cta & 7)) * (64 * 512) + hkv * 8 * 512));
    }

    if (wg == 1) bar_arrive(kBarTurn0, 256);

    const uint32_t sQw = sQ + wg * 32768;
    Ring r{0, 0};
    STAMP(0);

    {
        float acc[128];
        const bool refiller = (warp8 & 3) == 0;
        auto release = [&](int t) {
            mbar_arrive_elect(sFull + kEmpty1 + 8 * t);
            if (refiller) {
                mbar_wait(sFull + kEmpty1 + 8 * t, 0);
                if (elect_one()) {
                    const uint32_t slot = t % kSlots;
                    if (t + kSlots < kWTiles) ld.wq(t + kSlots, slot);
                    else if (t + kSlots - kWTiles < KV_EAGER) ld.kv(t + kSlots - kWTiles, slot);
                }
                __syncwarp();
            }
        };
        int prev = 0;
#pragma unroll 1
        for (int kc = 0; kc < 8; kc++) {
            const int t = wg ? wq_tile(1, kc) : wq_tile(0, kc);
            QSTEP(kc, 0);
            if (wg) mbar_wait(sFull + kFull1 + 8 * wq_tile(0, kc), 0);
            mbar_wait(sFull + kFull1 + 8 * t, 0);
            QSTEP(kc, 1);
            if (kc == 0) STAMP(1);
            const desc_t da = mkdesc(sQ + kc * 8192, 16);
            const desc_t db = mkdesc(sRing + (t % kSlots) * kSlotBytes, 8192);
            wg_fence();
            wgmma_ss_n256_tb<0, 0>(acc, da, db, kc > 0);
            wgmma_ss_n256_tb<32, 2048>(acc, da, db, 1);
            wgmma_ss_n256_tb<64, 4096>(acc, da, db, 1);
            wgmma_ss_n256_tb<96, 6144>(acc, da, db, 1);
            wg_commit();
            QSTEP(kc, 2);
            wg_wait<1>();
            QSTEP(kc, 3);
            if (kc > 0 && (!SKIPREL || prev < kWTiles - kSlots + KV_EAGER)) release(prev);
            QSTEP(kc, 4);
            prev = t;
            if (PF_W == 3 && (warp8 & 3) == 3 && 2 * kc + wg + kSlots + PF_WD < kWTiles) ld.wq_share(prm.ptrs, 2 * kc + wg + kSlots + PF_WD);
            if (PF_KV > 0) {
                const int n = 2 * kc + wg, w = warp8 & 3;
                const int cnt = (int)((PF_TAB >> (4 * n)) & 15);
                const int u = (int)(((n < 8 ? kPfLo : kPfHi) >> (8 * (n & 7))) & 255) + w;
                if (w < cnt) {
                    const int cta = cta_id();
                    prefetch_line(prm.ptrs[(cta >> 6) * 5 + 1 + ((u >> 3) & 1)] +
                                  ((size_t)KVROW(((cta & 7) * kHkv + ((cta >> 3) & 7)) * kSk) + (u >> 4) * kTileN) * 256 + (u & 7) * 4096 +
                                  (threadIdx.x & 31) * 128);
                }
            }
        }
        wg_wait<0>();
        reg_fence(acc);
        if (!SKIPREL) release(prev);
        QSTEP(8, 0);
        STAMP(2);
        if (threadIdx.x == 160) asm volatile("st.shared.u32 [%0], %1;" ::"r"(sFull + kEpoch), "r"(epoch0) : "memory");
        uint32_t q[64];
#pragma unroll
        for (int i = 0; i < 64; i++) q[i] = pack_bf16(acc[2 * i], acc[2 * i + 1]);
        if (wg == 0) {
            mbar_wait(sFull + kEmpty1 + 8 * wq_tile(1, 3), 0);
            bar_arrive(kBarAll, 256);
        } else {
            bar_sync(kBarAll, 256);
        }
        QSTEP(8, 1);
        store_head(sQw, q);
        store_head(sQw + 16384, q + 32);
        QSTEP(8, 2);
        fence_async_smem();
        QSTEP(8, 3);
        bar_sync_sel<kBarWg0, kBarWg1, 128>(wg);
    }
    r.slot = kWTiles % kSlots;
    QSTEP(8, 4);
    STAMP(3);

    uint32_t op[64];
    uint32_t vslot = 0;
    {
        float oa[64], ob[64], s[64];
        uint32_t p[32];
        float ma[2] = {-INFINITY, -INFINITY}, mb[2] = {-INFINITY, -INFINITY};
        float la[2] = {0.f, 0.f}, lb[2] = {0.f, 0.f};
#pragma unroll
        for (int i = 0; i < 64; i++) { oa[i] = 0.f; ob[i] = 0.f; }
        const desc_t dqa = mkdesc(sQw, 16), dqb = dqa + (16384 >> 4);
        const desc_t dk0 = mkdesc(sRing, 16), dv0 = mkdesc(sRing, 16384);
        constexpr uint32_t kSlotDesc = kSlotBytes >> 4;
        SoftmaxTmp t;
        const CUtensorMap* mapK = prm.maps + (blockIdx.x >> 6) * 5 + 1;
        const int kvrow = KVROW(((blockIdx.x & 7) * kHkv + ((blockIdx.x >> 3) & 7)) * kSk) + 2 * kTileN;
        uint32_t opaque;
        asm volatile("mov.u32 %0, %%nsmid;" : "=r"(opaque));

        uint32_t kslot = r.slot;
        mbar_wait(sFull + 8 * r.slot, r.phase);
        r.advance();
        QSTEP(8, 5);
        STAMP(4);
        bar_sync_sel<kBarTurn0, kBarTurn1, 256>(wg);
        STEP(0, 0);
        wg_fence();
        issue_qk(s, dqa, dk0 + kslot * kSlotDesc);
        bar_arrive_sel<kBarTurn1, kBarTurn0, 256>(wg);
        if (KV_EAGER < 4 && loader && elect_one()) ld.kv(KV_EAGER, (kWTiles + KV_EAGER) % kSlots);
        STEP(0, 1);
        wg_wait<0>();
        STEP(0, 2);
        reg_fence(s);
        QSTEP(9, 0);
        softmax_ref(true, FIRSTFAST, s, oa, ma, la, t);
        QSTEP(9, 1);
        if (KV_EAGER == 2 && V1_AT == 0 && loader && elect_one()) ld.kv(3, (kWTiles + 3) % kSlots);
        softmax_exp<0, 16>(s, t);
        softmax_pack(p, s, la, t);
        QSTEP(9, 2);
        if (KV_EAGER == 2 && V1_AT == 1 && loader && elect_one()) ld.kv(3, (kWTiles + 3) % kSlots);

#pragma unroll 1
        for (int j = 0; j < kKvTiles; j++) {
            const uint32_t vprev = vslot;
            vslot = r.slot;
            reg_fence(oa);
            reg_fence(p);
            STEP(2 * j, 5);
            bar_sync_sel<kBarTurn0, kBarTurn1, 256>(wg);
            STEP(2 * j + 1, 0);
            wg_fence();
            issue_qk(s, dqb, dk0 + kslot * kSlotDesc);
            tma_refill(loader && (KV_EAGER < 5 || j > 0) && j < kKvTiles - 2, sRing + vprev * kSlotBytes, mapK, kvrow + j * kTileN, sFull + 8 * vprev);
            if (j >= kKvTiles - 2 && loader && elect_one()) ld.wo(2 * j + 4 - 2 * kKvTiles, vprev);
            if (2 * j + 1 >= PF_WO_S0) ld.wo_share(prm.ptrs, 2 * j + 1, warp8);
            mbar_wait(sFull + 8 * r.slot, r.phase);
            r.advance();
            wg_fence();
            issue_pv_from<0, PVSPLIT>(oa, p, dv0 + vslot * kSlotDesc);
            wg_commit();
            STEP(2 * j + 1, 1);
            wg_wait<1>();
            STEP(2 * j + 1, 2);
            reg_fence(s);
            {
                const bool unsafe = softmax_check(s, mb);
                wg_fence();
                issue_pv_from<PVSPLIT, 8>(oa, p, dv0 + vslot * kSlotDesc);
                wg_commit();
                bar_arrive_sel<kBarTurn1, kBarTurn0, 256>(wg);
                softmax_ref(unsafe, FIRSTFAST && j == 0, s, ob, mb, lb, t);
            }
            softmax_exp<0, SPLIT>(s, t);
            reg_fence(s);
            STEP(2 * j + 1, 3);
            sched_break<4 * SPLIT>(opaque, s);
            wg_wait<0>();
            STEP(2 * j + 1, 4);
            const Ring kn = r;
            const bool k_ready = mbar_test(sFull + 8 * kn.slot, kn.phase);
            r.advance();
            reg_fence(oa);
            reg_fence(s);
            softmax_exp<SPLIT, 16>(s, t);
            softmax_pack(p, s, lb, t);
            if (j == kKvTiles - 1) break;

            const uint32_t kprev = kslot;
            kslot = kn.slot;
            if (!k_ready) mbar_wait(sFull + 8 * kn.slot, kn.phase);
            reg_fence(ob);
            reg_fence(p);
            STEP(2 * j + 1, 5);
            bar_sync_sel<kBarTurn0, kBarTurn1, 256>(wg);
            STEP(2 * j + 2, 0);
            wg_fence();
            issue_qk(s, dqa, dk0 + kslot * kSlotDesc);
            tma_refill(loader && j < kKvTiles - 2, sRing + kprev * kSlotBytes, mapK + 1, kvrow + j * kTileN, sFull + 8 * kprev);
            if (j >= kKvTiles - 2 && loader && elect_one()) ld.wo(2 * j + 5 - 2 * kKvTiles, kprev);
            if (2 * j + 2 >= PF_WO_S0) ld.wo_share(prm.ptrs, 2 * j + 2, warp8);
            wg_fence();
            issue_pv_from<0, PVSPLIT>(ob, p, dv0 + vslot * kSlotDesc);
            wg_commit();
            STEP(2 * j + 2, 1);
            wg_wait<1>();
            STEP(2 * j + 2, 2);
            reg_fence(s);
            {
                const bool unsafe = softmax_check(s, ma);
                wg_fence();
                issue_pv_from<PVSPLIT, 8>(ob, p, dv0 + vslot * kSlotDesc);
                wg_commit();
                bar_arrive_sel<kBarTurn1, kBarTurn0, 256>(wg);
                softmax_ref(unsafe, false, s, oa, ma, la, t);
            }
            softmax_exp<0, SPLIT>(s, t);
            reg_fence(s);
            STEP(2 * j + 2, 3);
            sched_break<4 * SPLIT>(opaque, s);
            wg_wait<0>();
            STEP(2 * j + 2, 4);
            reg_fence(ob);
            reg_fence(s);
            softmax_exp<SPLIT, 16>(s, t);
            softmax_pack(p, s, la, t);
        }
        reg_fence(ob);
        reg_fence(p);
        bar_sync_sel<kBarTurn0, kBarTurn1, 256>(wg);
        wg_fence();
        issue_pv(ob, p, dv0 + vslot * kSlotDesc);
        if (loader && elect_one()) ld.wo(3, kslot);
        if (PF_WO_END) {
            ld.wo_tile_share(prm.ptrs, 4 + warp8);
            if (PF_WO_END > 1 && warp8 >= 4) ld.wo_tile_share(prm.ptrs, 8 + warp8);
        }
        if (wg == 0) bar_arrive(kBarTurn1, 256);
        finalize_head(op, oa, la);
        store_head(sQw, op);
        wg_wait<0>();
        reg_fence(ob);
        if (elect_one()) {
            mbar_arrive(sFull + kEmptyV);
            if (loader) {
                mbar_wait(sFull + kEmptyV, 0);
                ld.wo(4, vslot);
            }
        }
        __syncwarp();
        finalize_head(op + 32, ob, lb);
        store_head(sQw + 16384, op + 32);
    }
    STAMP(5);

    {
        const int cta = cta_id();
        const int hkv = (cta >> 3) & 7;
        const int tid = threadIdx.x & 127, lane = tid & 31, warp = warp8 & 3;
        fence_async_smem();
        bar_arrive_sel<kBarWg1, kBarWg0, 256>(wg);
        uint32_t epoch;
        asm volatile("ld.shared.u32 %0, [%1];" : "=r"(epoch) : "r"(sFull + kEpoch) : "memory");
        const uint32_t tag = ~epoch & 1u;
        uint4* group = prm.inbox + (size_t)((cta >> 6) * 8 + (cta & 7)) * (64 * 512);
        uint4* inbox = group + hkv * (8 * 512);
        reg_fence(op);
        const desc_t dA = mkdesc(sQ + (wg ^ 1) * 32768, 16);
        const CUtensorMap* mapWo = prm.maps + (cta >> 6) * 5 + 4;
        float acc[32];
        uint4 in[7][4];
        uint32_t polls = 0, flags = 0;

        auto release = [&](int t, uint32_t slot, int who) {
            mbar_arrive_elect(sFull + kEmpty3 + 8 * t);
            if (warp == who) {
                const int u = t + kSlots;
                mbar_wait(sFull + kEmpty3 + 8 * t, 0);
                tma3d_elect(sRing + slot * kSlotBytes, mapWo, hkv * 512 + (((u >> 1) ^ u) & 1) * 256, (hkv + 1 + (u >> 1)) & 7,
                            sFull + kFull3 + 8 * u, kSlotBytes);
            }
        };
        auto stale = [&](const uint4 (&v)[4]) { return (v[0].x ^ tag) | (v[1].x ^ tag) | (v[2].x ^ tag) | (v[3].x ^ tag); };
        auto poll = [&](uint4 (&v)[4], int k) {
            while (__any_sync(0xffffffffu, (stale(v) & 1u) != 0) && polls < kPollLimit) {
                polls++;
#pragma unroll
                for (int q = 0; q < 4; q++) v[q] = ld_packet(inbox + k * 512 + q * 128 + tid);
            }
        };
        auto stage = [&](int k) { return k <= 4 ? sRing + 4 * kSlotBytes + (k - 1) * 8192 : sRing + (k - 5) * 8192; };
        auto smem_fetch = [&](uint4 (&v)[4], int k) {
#pragma unroll
            for (int q = 0; q < 4; q++)
                asm volatile("ld.shared.v4.u32 {%0, %1, %2, %3}, [%4];" : "=r"(v[q].x), "=r"(v[q].y), "=r"(v[q].z), "=r"(v[q].w)
                             : "r"(stage(k) + q * 2048 + tid * 16) : "memory");
        };
        const uint32_t* myflags = reinterpret_cast<const uint32_t*>(inbox + 8) + lane;
        auto have = [&](uint32_t mask) { return (__ballot_sync(0xffffffffu, flags == epoch + 1) & mask) == mask; };
        bool got_a = false, got_b = false;
        auto collect = [&](uint32_t mask, int k0, int n, uint32_t bar) {
            while (!have(mask) && polls < kPollLimit) {
                polls++;
                flags = ld_flag(myflags);
            }
            bulk_load_elect(stage(k0), inbox + k0 * 512, n * 8192, bar);
        };

        auto early_a = [&](int ps) {
            if (ps == 3 && warp8 == 2 && have(0x000ffff0u)) {
                mbar_wait(sFull + kEmpty3 + 8 * 11, 0);
                collect(0x000ffff0u, 1, 4, sFull + kBulk);
                got_a = true;
            }
        };
        auto early_b = [&](int ps) {
            if (ps == 3 && warp8 == 2 && got_a && have(0xfff00000u)) {
                mbar_wait(sFull + kEmpty3 + 8 * 13, 0);
                mbar_arrive_elect(sFull + kBulk + 16);
                collect(0xfff00000u, 5, 3, sFull + kBulk + 8);
                got_b = true;
            }
        };

#pragma unroll
        for (int ps = 0; ps < 4; ps++) {
            const int t0 = 4 * ps + 2 * wg;
            const uint32_t slot0 = wg ? (5 + 4 * ps) % kSlots : (3 + 4 * ps) % kSlots;
            const uint32_t slot1 = wg ? (6 + 4 * ps) % kSlots : (4 + 4 * ps) % kSlots;
            OSTEP(ps, 0);
            mbar_wait(sFull + kFull3 + 8 * t0, 0);
            OSTEP(ps, 1);
            if (ps > 0) bar_sync_sel<kBarTurn0, kBarTurn1, 256>(wg);
            wg_fence();
            issue_oproj_rs<0, true>(acc, op, mkdesc(sRing + slot0 * kSlotBytes, 16));
            wg_commit();
            OSTEP(ps, 2);
            if (COLLECT_AT == 0) early_a(ps);
            if (ps == 0) bar_sync_sel<kBarWg0, kBarWg1, 256>(wg);
            mbar_wait(sFull + kFull3 + 8 * (t0 + 1), 0);
            OSTEP(ps, 3);
            wg_fence();
            issue_oproj_ss<0>(acc, dA, mkdesc(sRing + slot1 * kSlotBytes, 16));
            wg_commit();
            if (wg == 0 ? ps > 0 : ps < 3) bar_arrive_sel<kBarTurn1, kBarTurn0, 256>(wg);
            OSTEP(ps, 4);
            if (COLLECT_AT == 1) early_a(ps);
            if (warp8 == 2 && (ps == 0 || ps == 3)) flags = ld_flag(myflags);
            if (ps < 3) {
                wg_wait<1>();
                if (t0 + kSlots < kWTiles) release(t0, slot0, 0);
            } else if (wg == 1) {
                mbar_wait(sFull + kBulk, 0);
#pragma unroll
                for (int k = 1; k <= 4; k++) smem_fetch(in[k - 1], k);
            }
            wg_wait<0>();
            reg_fence(acc);
            OSTEP(ps, 5);
            if (ps < 3 && t0 + 1 + kSlots < kWTiles) release(t0 + 1, slot1, 1);
            if (ps == 3) STAMP(6); else STAMP(10 + ps);
            if (ps == (wg ? 2 : 3)) mbar_arrive_elect(sFull + kEmpty3 + 8 * (t0 + 1));
            if (!SENDFIRST) early_b(ps);
            if (ps < 3 || wg == 0) {
                const int k = 1 + 2 * ps + wg;
                uint4* box = group + ((hkv + k) & 7) * (8 * 512);
#pragma unroll
                for (int q = 0; q < 4; q++) {
                    const float big = __fmul_rn(acc[8 * q], 131073.f);
                    const float e0 = __fsub_rn(big, __fsub_rn(big, acc[8 * q]));
                    st_packet(box + k * 512 + q * 128 + tid, (pack_bf16(e0, acc[8 * q + 1]) & ~1u) | tag, pack_bf16(acc[8 * q + 2], acc[8 * q + 3]),
                              pack_bf16(acc[8 * q + 4], acc[8 * q + 5]), pack_bf16(acc[8 * q + 6], acc[8 * q + 7]));
                }
                st_flag_elect(reinterpret_cast<uint32_t*>(box + 8) + k * 4 + warp, epoch + 1);
            }
            if (ps == 2 && warp8 == 2) flags = ld_flag(myflags);
            if (SENDFIRST) early_b(ps);
            if (ps == 3 && warp8 == 2 && !got_b) {
                mbar_wait(sFull + kEmpty3 + 8 * 11, 0);
                mbar_wait(sFull + kEmpty3 + 8 * 13, 0);
                if (!got_a) collect(0x000ffff0u, 1, 4, sFull + kBulk);
                collect(0x0ff00000u, 5, 2, sFull + kBulk + 8);
                collect(0xf0000000u, 7, 1, sFull + kBulk + 16);
                if (polls >= kPollLimit) __trap();
            }
        }
        STAMP(7);
        OSTEP(4, 0);

        if (wg == 1) {
            const uint32_t sel = lane >> 2, pos = (lane & 3) * 2;
            const uint32_t ident = sel == pos ? 0x00003f80u : (sel == pos + 1 ? 0x3f800000u : 0u);
            auto add_two = [&](const uint4 (&u)[4], const uint4 (&v)[4]) {
#pragma unroll
                for (int q = 0; q < 4; q++) {
                    mma_16816(acc + 8 * q, u[q].x & ~1u, u[q].y, v[q].x & ~1u, v[q].y, ident, ident);
                    mma_16816(acc + 8 * q + 4, u[q].z, u[q].w, v[q].z, v[q].w, ident, ident);
                }
            };
            if (__any_sync(0xffffffffu, ((stale(in[0]) | stale(in[1]) | stale(in[2]) | stale(in[3])) & 1u) != 0)) {
#pragma unroll
                for (int k = 1; k <= 4; k++) poll(in[k - 1], k);
            }
            add_two(in[0], in[1]);
            add_two(in[2], in[3]);
            OSTEP(4, 1);
            mbar_wait(sFull + kBulk + 8, 0);
            OSTEP(4, 2);
            smem_fetch(in[4], 5);
            smem_fetch(in[5], 6);
            if (__any_sync(0xffffffffu, ((stale(in[4]) | stale(in[5])) & 1u) != 0)) {
                poll(in[4], 5);
                poll(in[5], 6);
            }
            add_two(in[4], in[5]);
            OSTEP(4, 3);
            mbar_wait(sFull + kBulk + 16, 0);
            smem_fetch(in[6], 7);
            poll(in[6], 7);
#pragma unroll
            for (int q = 0; q < 4; q++) {
                mma_16816(acc + 8 * q, in[6][q].x & ~1u, in[6][q].y, in[6][q].z, in[6][q].w, ident, 0u);
                mma_16816(acc + 8 * q + 4, in[6][q].x & ~1u, in[6][q].y, in[6][q].z, in[6][q].w, 0u, ident);
            }
            if (polls >= kPollLimit) __trap();
            OSTEP(4, 4);
            STAMP(8);
            const uint32_t sOut = sRing + kSlotBytes;
            const int srow = warp * 16 + (lane & 7) + ((lane >> 3) & 1) * 8;
#pragma unroll
            for (int k = 0; k < 4; k++)
                stmatrix_x4(sOut + srow * 128 + (((2 * k + (lane >> 4)) ^ (srow & 7)) << 4), pack_bf16(acc[8 * k], acc[8 * k + 1]),
                            pack_bf16(acc[8 * k + 2], acc[8 * k + 3]), pack_bf16(acc[8 * k + 4], acc[8 * k + 5]),
                            pack_bf16(acc[8 * k + 6], acc[8 * k + 7]));
            __syncwarp();
            __nv_bfloat16* dst = prm.out + (size_t)((cta & 7) * kSq) * 1024 + (cta >> 6) * 512 + hkv * 64 + (lane & 7) * 8;
#pragma unroll
            for (int k = 0; k < 4; k++) {
                const int row = warp * 16 + k * 4 + (lane >> 3);
                uint4 v;
                asm volatile("ld.shared.v4.u32 {%0, %1, %2, %3}, [%4];" : "=r"(v.x), "=r"(v.y), "=r"(v.z), "=r"(v.w)
                             : "r"(sOut + row * 128 + (((lane & 7) ^ (row & 7)) << 4)) : "memory");
                *reinterpret_cast<uint4*>(dst + (size_t)row * 1024) = v;
            }
        } else {
            STAMP(8);
            if (tid == 0) __stcg(reinterpret_cast<uint32_t*>(inbox), epoch + 1);
        }
    }
    OSTEP(4, 5);
    STAMP(9);
}

typedef CUresult (*EncodeFn)(CUtensorMap*, CUtensorMapDataType, cuuint32_t, void*, const cuuint64_t*, const cuuint64_t*,
                             const cuuint32_t*, const cuuint32_t*, CUtensorMapInterleave, CUtensorMapSwizzle,
                             CUtensorMapL2promotion, CUtensorMapFloatOOBfill);

void encode_map(EncodeFn fn, CUtensorMap* m, void* ptr, uint64_t rows, uint64_t cols, uint32_t box_rows, uint32_t box_blocks) {
    cuuint64_t dims[3] = {64, rows, cols / 64};
    cuuint64_t strides[2] = {cols * 2, 128};
    cuuint32_t box[3] = {64, box_rows, box_blocks};
    cuuint32_t es[3] = {1, 1, 1};
    fn(m, CU_TENSOR_MAP_DATA_TYPE_BFLOAT16, 3, ptr, dims, strides, box, es, CU_TENSOR_MAP_INTERLEAVE_NONE,
       CU_TENSOR_MAP_SWIZZLE_128B, CU_TENSOR_MAP_L2_PROMOTION_L2_128B, CU_TENSOR_MAP_FLOAT_OOB_FILL_NONE);
}

}

extern "C" void kernel_launch(void* const* d_in, const int* in_sizes, int n_in, void* d_out, int out_size) {
    (void)in_sizes; (void)n_in; (void)out_size;
    static EncodeFn fn = nullptr;
    static uint4* inbox = nullptr;
    if (!fn) {
        cudaGetSymbolAddress((void**)&inbox, g_inbox);
        cudaDriverEntryPointQueryResult qr;
        cudaGetDriverEntryPoint("cuTensorMapEncodeTiled", (void**)&fn, cudaEnableDefault, &qr);
        cudaFuncSetAttribute(fused_gqa_kernel, cudaFuncAttributeMaxDynamicSharedMemorySize, kSmemBytes);
    }
    Params prm;
    for (int br = 0; br < 2; br++) {
        void* const* in = d_in + br * 5;
        for (int i = 0; i < 5; i++) prm.ptrs[br * 5 + i] = (const uint8_t*)in[i];
        encode_map(fn, &prm.maps[br * 5 + 0], in[0], kB * kSq, kD, 64, 1);
        encode_map(fn, &prm.maps[br * 5 + 1], in[1], (uint64_t)kB * kHkv * kSk, kDh, kTileN, 2);
        encode_map(fn, &prm.maps[br * 5 + 2], in[2], (uint64_t)kB * kHkv * kSk, kDh, kTileN, 2);
        encode_map(fn, &prm.maps[br * 5 + 3], in[3], kD, kHq * kDh, 64, 4);
        encode_map(fn, &prm.maps[br * 5 + 4], in[4], kHq * kDh, kD, 256, 1);
    }
    prm.inbox = inbox;
    prm.out = (__nv_bfloat16*)d_out;
    fused_gqa_kernel<<<128, kThreads, kSmemBytes, cudaStreamPerThread>>>(prm);
}
```
